```python
import torch

def _softmax(x, axis=-1):
    return torch.softmax(x, dim=axis)
def _gelu(x):
    return torch.nn.functional.gelu(x, approximate="tanh")
def _silu(x):
    return torch.nn.functional.silu(x)
def _sigmoid(x):
    return torch.sigmoid(x)
def _layernorm(x, axis=-1, eps=1e-5):
    m = x.mean(dim=axis, keepdim=True)
    v = x.var(dim=axis, keepdim=True, unbiased=False)
    return (x - m) / torch.sqrt(v + eps)
def _scatter_add(tgt, idx, src, axis=0):
    return tgt.clone().index_add_(axis, idx, src)
def _segment_sum(src, seg, n):
    out = torch.zeros((n,) + src.shape[1:], dtype=src.dtype)
    return out.index_add_(0, seg, src)
def _pad(x, pw):
    flat = tuple(v for pair in reversed(pw) for v in pair)
    return torch.nn.functional.pad(x, flat)

kernel_name = 'concat_heads__linear_kernel_hedgehog__compressed_kv_cla__prompt'

def setup_inputs():

    _w = (lambda a: (lambda t: t.to(torch.bfloat16) if t.is_floating_point() else t)(torch.as_tensor(a)))
    def _A_setup():
        B, S, D, H = 1, 2048, 512, 32
        Dh = D // H
        return {
            "x": _w((lambda *s: torch.randn(*s, dtype=torch.bfloat16) * 0.4)(B, S, D)),
            "wqkv": _w((lambda *s: torch.randn(*s, dtype=torch.bfloat16) * 0.4)(D, 3 * D)),
            "w_phi": _w((lambda *s: torch.randn(*s, dtype=torch.bfloat16) * 0.4)(H, Dh, Dh) * (Dh ** -0.5)),
            "wo": _w((lambda *s: torch.randn(*s, dtype=torch.bfloat16) * 0.05)(D, D)),
        }
    _A_in = _A_setup()

    def _B_setup():
        B, H, Sq, Sk, D, M = 1, 32, 2048, 2048, 128, 512
        Dc = 4 * D
        return {
            "x": _w((lambda *s: torch.randn(*s, dtype=torch.bfloat16) * 0.8)(B, Sq, M)),
            "c_kv": _w((lambda *s: torch.randn(*s, dtype=torch.bfloat16) * 0.4)(B, Sk, Dc)),
            "w_q": _w((lambda *s: torch.randn(*s, dtype=torch.bfloat16) * 6.4)(M, H, D) * (M ** -0.5)),
            "w_uk": _w((lambda *s: torch.randn(*s, dtype=torch.bfloat16) * 6.4)(Dc, H, D) * (Dc ** -0.5)),
            "w_uv": _w((lambda *s: torch.randn(*s, dtype=torch.bfloat16) * 0.4)(Dc, H, D) * (Dc ** -0.5)),
            "w_o": _w((lambda *s: torch.randn(*s, dtype=torch.bfloat16) * 0.4)(H, D, M) * ((H * D) ** -0.5)),
        }
    _B_in = _B_setup()

    return {
        "A_x": _A_in["x"],
        "A_wqkv": _A_in["wqkv"],
        "A_w_phi": _A_in["w_phi"],
        "A_wo": _A_in["wo"],
        "B_x": _B_in["x"],
        "B_c_kv": _B_in["c_kv"],
        "B_w_q": _B_in["w_q"],
        "B_w_uk": _B_in["w_uk"],
        "B_w_uv": _B_in["w_uv"],
        "B_w_o": _B_in["w_o"],
    }

def reference(A_x, A_wqkv, A_w_phi, A_wo, B_x, B_c_kv, B_w_q, B_w_uk, B_w_uv, B_w_o):
    def _A_ref(x, wqkv, w_phi, wo):
        B, S, D = x.shape
        H = 32; Dh = D // H
        qkv = (lambda x, *d: x.permute(*d))((x @ wqkv).reshape(B, S, 3, H, Dh), 2, 0, 3, 1, 4)
        q, k, v = qkv[0], qkv[1], qkv[2]
        pq = torch.einsum("bhsd,hdf->bhsf", q, w_phi)
        pk = torch.einsum("bhsd,hdf->bhsf", k, w_phi)
        phi_q = torch.concatenate([_softmax(pq, axis=-1), _softmax(-pq, axis=-1)], axis=-1)
        phi_k = torch.concatenate([_softmax(pk, axis=-1), _softmax(-pk, axis=-1)], axis=-1)
        kv = torch.einsum("bhsf,bhsd->bhfd", phi_k, v)
        z  = torch.einsum("bhsf->bhf", phi_k)
        num = torch.einsum("bhqf,bhfd->bhqd", phi_q, kv)
        den = torch.einsum("bhqf,bhf->bhq", phi_q, z)[..., None] + 1e-6
        o = num / den
        return (lambda x, *d: x.permute(*d))(o, 0, 2, 1, 3).reshape(B, S, D) @ wo

    def _B_ref(x, c_kv, w_q, w_uk, w_uv, w_o):
        B, Sq, M = x.shape[0], x.shape[1], x.shape[2]
        Sk = c_kv.shape[1]
        H, D = w_q.shape[1], w_q.shape[2]
        q = torch.einsum("bqm,mhd->bhqd", x, w_q)
        k = torch.einsum("bkc,chd->bhkd", c_kv, w_uk)
        v = torch.einsum("bkc,chd->bhkd", c_kv, w_uv)
        scores = torch.einsum("bhqd,bhkd->bhqk", q, k) * (D ** -0.5)
        off = Sk - Sq
        qi = torch.arange(Sq)[:, None]
        kj = torch.arange(Sk)[None, :]
        cmask = kj <= (qi + off)
        scores = torch.where(cmask[None, None], scores, -1e9)
        p = _softmax(scores, axis=-1)
        ctx = torch.einsum("bhqk,bhkd->bhqd", p, v)
        return torch.einsum("bhqd,hdm->bqm", ctx, w_o)

    a = _A_ref(A_x, A_wqkv, A_w_phi, A_wo)
    b = _B_ref(B_x, B_c_kv, B_w_q, B_w_uk, B_w_uv, B_w_o)
    return torch.concatenate([a, b], axis=-1)
```

```cpp
#include <cuda_runtime.h>
#include <cuda_bf16.h>
#include <cuda.h>
#include <stdint.h>
#include <string.h>

namespace {

constexpr int NSLOT = 6;
constexpr int SLOT_BYTES = 32768;
constexpr int STG_OFF = NSLOT * SLOT_BYTES;
constexpr int BAR_OFF = STG_OFF + 32768;
constexpr int SMEM_BYTES = BAR_OFF + 256 + 1024;
constexpr int MAX_CLUSTERS = 66;
constexpr int MAX_ITEMS = 16;
constexpr uint32_t SPIN_LIMIT = 1u << 20;

constexpr int BAR_FULL = 0;
constexpr int BAR_EMPTY = 64;
constexpr int BAR_STG_FULL = 128;
constexpr int BAR_STG_EMPTY = 144;

enum { T_KV = 0, T_ATT = 1, T_OP = 2, T_A1 = 3, T_A2 = 4, T_A3 = 5, T_END = 7 };

constexpr int F_KV = 0;
constexpr int F_CTX = 256;
constexpr int F_AKV = 512;
constexpr int F_O = 544;
constexpr int F_TOTAL = 576;

struct Params {
    CUtensorMap tm_xb64;
    CUtensorMap tm_ckv;
    CUtensorMap tm_xa;
    CUtensorMap tm_wq, tm_wuk, tm_wuv, tm_wo, tm_awqkv, tm_awo;
    CUtensorMap tm_out;
    const __nv_bfloat16* w_phi;
    uint16_t sched[MAX_CLUSTERS][MAX_ITEMS];
};

__device__ __align__(1024) uint8_t g_K[32 * 16 * SLOT_BYTES];
__device__ __align__(1024) uint8_t g_V[32 * 16 * SLOT_BYTES];
__device__ __align__(1024) uint8_t g_ctx[16 * 32 * SLOT_BYTES];
__device__ __align__(1024) uint8_t g_o[16 * 4 * SLOT_BYTES];
__device__ __align__(1024) float g_akv[2][32 * 17 * 32];
__device__ uint32_t g_flags[F_TOTAL];
__device__ uint32_t g_epoch[2 * MAX_CLUSTERS];

__device__ __forceinline__ uint32_t smem_u32(const void* p) { return (uint32_t)__cvta_generic_to_shared(p); }
__device__ __forceinline__ void abort_launch() { asm volatile("st.global.u32 [%0], %1;" ::"l"(0ull), "r"(0) : "memory"); }
__device__ __forceinline__ void mbar_init(uint32_t a, uint32_t c) {
    asm volatile("mbarrier.init.shared::cta.b64 [%0], %1;" ::"r"(a), "r"(c) : "memory");
}
__device__ __forceinline__ bool mbar_try(uint32_t a, uint32_t ph) {
    uint32_t ok;
    asm volatile("{\n.reg .pred p;\nmbarrier.try_wait.parity.shared::cta.b64 p, [%1], %2;\nselp.u32 %0, 1, 0, p;\n}"
                 : "=r"(ok) : "r"(a), "r"(ph) : "memory");
    return ok;
}
__device__ __forceinline__ void mbar_wait(uint32_t a, uint32_t ph) {
    if (mbar_try(a, ph)) return;
    uint32_t n = 0;
    while (!mbar_try(a, ph)) {
        if (++n > SPIN_LIMIT) { abort_launch(); break; }
    }
}
__device__ __forceinline__ void mbar_arrive(uint32_t a) {
    asm volatile("mbarrier.arrive.shared::cta.b64 _, [%0];" ::"r"(a) : "memory");
}
__device__ __forceinline__ void mbar_arrive_cta(uint32_t a, uint32_t cta) {
    asm volatile("{\n.reg .b32 r;\nmapa.shared::cluster.u32 r, %0, %1;\nmbarrier.arrive.shared::cluster.b64 _, [r];\n}"
                 ::"r"(a), "r"(cta) : "memory");
}
__device__ __forceinline__ void mbar_expect(uint32_t a, uint32_t bytes) {
    asm volatile("mbarrier.arrive.expect_tx.shared::cta.b64 _, [%0], %1;" ::"r"(a), "r"(bytes) : "memory");
}
__device__ __forceinline__ void tma_2d(uint32_t dst, const CUtensorMap* tm, int c0, int c1, uint32_t bar) {
    asm volatile("cp.async.bulk.tensor.2d.shared::cluster.global.mbarrier::complete_tx::bytes [%0], [%1, {%3, %4}], [%2];"
                 ::"r"(dst), "l"(tm), "r"(bar), "r"(c0), "r"(c1) : "memory");
}
__device__ __forceinline__ void tma_2d_mc(uint32_t dst, const CUtensorMap* tm, int c0, int c1, uint32_t bar) {
    asm volatile("cp.async.bulk.tensor.2d.shared::cluster.global.mbarrier::complete_tx::bytes.multicast::cluster [%0], [%1, {%3, %4}], [%2], %5;"
                 ::"r"(dst), "l"(tm), "r"(bar), "r"(c0), "r"(c1), "h"((uint16_t)3) : "memory");
}
__device__ __forceinline__ void bulk_load(uint32_t dst, const void* src, uint32_t bytes, uint32_t bar) {
    asm volatile("cp.async.bulk.shared::cluster.global.mbarrier::complete_tx::bytes [%0], [%1], %2, [%3];"
                 ::"r"(dst), "l"(src), "r"(bytes), "r"(bar) : "memory");
}
__device__ __forceinline__ void bulk_load_mc(uint32_t dst, const void* src, uint32_t bytes, uint32_t bar) {
    asm volatile("cp.async.bulk.shared::cluster.global.mbarrier::complete_tx::bytes.multicast::cluster [%0], [%1], %2, [%3], %4;"
                 ::"r"(dst), "l"(src), "r"(bytes), "r"(bar), "h"((uint16_t)3) : "memory");
}
__device__ __forceinline__ void bulk_store(void* dst, uint32_t src, uint32_t bytes) {
    asm volatile("cp.async.bulk.global.shared::cta.bulk_group [%0], [%1], %2;" ::"l"(dst), "r"(src), "r"(bytes) : "memory");
}
__device__ __forceinline__ void tma_store_2d(const CUtensorMap* tm, int c0, int c1, uint32_t src) {
    asm volatile("cp.async.bulk.tensor.2d.global.shared::cta.bulk_group [%0, {%2, %3}], [%1];"
                 ::"l"(tm), "r"(src), "r"(c0), "r"(c1) : "memory");
}
__device__ __forceinline__ void bulk_commit() { asm volatile("cp.async.bulk.commit_group;" ::: "memory"); }
__device__ __forceinline__ void bulk_wait_read() { asm volatile("cp.async.bulk.wait_group.read 0;" ::: "memory"); }
__device__ __forceinline__ void bulk_wait_all() { asm volatile("cp.async.bulk.wait_group 0;" ::: "memory"); }
__device__ __forceinline__ void fence_async_smem() { asm volatile("fence.proxy.async.shared::cta;" ::: "memory"); }
__device__ __forceinline__ void fence_async_global() { asm volatile("fence.proxy.async.global;" ::: "memory"); }
__device__ __forceinline__ uint32_t ld_acquire(const uint32_t* p) {
    uint32_t v;
    asm volatile("ld.acquire.gpu.global.u32 %0, [%1];" : "=r"(v) : "l"(p) : "memory");
    return v;
}
__device__ __forceinline__ void flag_signal(uint32_t* p) {
    asm volatile("red.release.gpu.global.add.u32 [%0], 1;" ::"l"(p) : "memory");
}
__device__ __forceinline__ void flag_wait(const uint32_t* p, uint32_t target) {
    uint32_t n = 0;
    while ((int32_t)(ld_acquire(p) - target) < 0) {
        if (++n > SPIN_LIMIT) { abort_launch(); break; }
        __nanosleep(32);
    }
}
__device__ __forceinline__ void bar_sync(int id, int n) { asm volatile("bar.sync %0, %1;" ::"r"(id), "r"(n) : "memory"); }
__device__ __forceinline__ void bar_arrive(int id, int n) { asm volatile("bar.arrive %0, %1;" ::"r"(id), "r"(n) : "memory"); }
__device__ __forceinline__ void cluster_sync() {
    asm volatile("barrier.cluster.arrive;\nbarrier.cluster.wait;" ::: "memory");
}
__device__ __forceinline__ uint32_t pack_bf16(float lo, float hi) {
    uint32_t r;
    asm("cvt.rn.bf16x2.f32 %0, %1, %2;" : "=r"(r) : "f"(hi), "f"(lo));
    return r;
}
__device__ __forceinline__ float round_bf16(float x) { return __bfloat162float(__float2bfloat16_rn(x)); }
__device__ __forceinline__ float ex2(float x) {
    float y;
    asm("ex2.approx.ftz.f32 %0, %1;" : "=f"(y) : "f"(x));
    return y;
}
__device__ __forceinline__ uint32_t movmatrix(uint32_t a) {
    uint32_t d;
    asm volatile("movmatrix.sync.aligned.m8n8.trans.b16 %0, %1;" : "=r"(d) : "r"(a));
    return d;
}
__device__ __forceinline__ void stmatrix_x4(uint32_t addr, uint32_t a, uint32_t b, uint32_t c, uint32_t d) {
    asm volatile("stmatrix.sync.aligned.m8n8.x4.shared.b16 [%0], {%1, %2, %3, %4};" ::"r"(addr), "r"(a), "r"(b), "r"(c), "r"(d) : "memory");
}
__device__ __forceinline__ void mma16816(float (&c)[4], uint32_t a0, uint32_t a1, uint32_t a2, uint32_t a3, uint32_t b0, uint32_t b1) {
    asm volatile("mma.sync.aligned.m16n8k16.row.col.f32.bf16.bf16.f32 {%0,%1,%2,%3}, {%4,%5,%6,%7}, {%8,%9}, {%0,%1,%2,%3};"
                 : "+f"(c[0]), "+f"(c[1]), "+f"(c[2]), "+f"(c[3]) : "r"(a0), "r"(a1), "r"(a2), "r"(a3), "r"(b0), "r"(b1));
}

__device__ __forceinline__ uint64_t make_desc(uint32_t addr, uint32_t lbo, uint32_t sbo) {
    return (uint64_t)((addr & 0x3FFFF) >> 4) | ((uint64_t)(lbo >> 4) << 16) | ((uint64_t)(sbo >> 4) << 32) | (1ull << 62);
}
__device__ __forceinline__ uint64_t desc_kmajor(uint32_t addr) { return make_desc(addr, 16, 1024); }
__device__ __forceinline__ uint64_t desc_nmajor(uint32_t addr, uint32_t lbo) { return make_desc(addr, lbo, 1024); }
__device__ __forceinline__ void wg_fence() { asm volatile("wgmma.fence.sync.aligned;" ::: "memory"); }
__device__ __forceinline__ void wg_commit() { asm volatile("wgmma.commit_group.sync.aligned;" ::: "memory"); }
template <int N> __device__ __forceinline__ void wg_wait() { asm volatile("wgmma.wait_group.sync.aligned %0;" ::"n"(N) : "memory"); }

#define R8(a, i) "+f"(a[i]), "+f"(a[i + 1]), "+f"(a[i + 2]), "+f"(a[i + 3]), "+f"(a[i + 4]), "+f"(a[i + 5]), "+f"(a[i + 6]), "+f"(a[i + 7])
#define R32(a, i) R8(a, i), R8(a, i + 8), R8(a, i + 16), R8(a, i + 24)
#define R64(a, i) R32(a, i), R32(a, i + 32)
#define L32A "%0,%1,%2,%3,%4,%5,%6,%7,%8,%9,%10,%11,%12,%13,%14,%15,%16,%17,%18,%19,%20,%21,%22,%23,%24,%25,%26,%27,%28,%29,%30,%31"
#define L32B "%32,%33,%34,%35,%36,%37,%38,%39,%40,%41,%42,%43,%44,%45,%46,%47,%48,%49,%50,%51,%52,%53,%54,%55,%56,%57,%58,%59,%60,%61,%62,%63"
#define L32C "%64,%65,%66,%67,%68,%69,%70,%71,%72,%73,%74,%75,%76,%77,%78,%79,%80,%81,%82,%83,%84,%85,%86,%87,%88,%89,%90,%91,%92,%93,%94,%95"
#define L32D "%96,%97,%98,%99,%100,%101,%102,%103,%104,%105,%106,%107,%108,%109,%110,%111,%112,%113,%114,%115,%116,%117,%118,%119,%120,%121,%122,%123,%124,%125,%126,%127"

template <int TB> __device__ __forceinline__ void wgmma_ss128(float (&d)[64], uint64_t da, uint64_t db, int acc) {
    asm volatile("{\n.reg .pred p;\nsetp.ne.b32 p, %66, 0;\n"
                 "wgmma.mma_async.sync.aligned.m64n128k16.f32.bf16.bf16 {" L32A "," L32B "}, %64, %65, p, 1, 1, 0, %67;\n}"
                 : R64(d, 0) : "l"(da), "l"(db), "r"(acc), "n"(TB));
}
template <int TB> __device__ __forceinline__ void wgmma_rs128(float (&d)[64], uint32_t a0, uint32_t a1, uint32_t a2, uint32_t a3, uint64_t db, int acc) {
    asm volatile("{\n.reg .pred p;\nsetp.ne.b32 p, %69, 0;\n"
                 "wgmma.mma_async.sync.aligned.m64n128k16.f32.bf16.bf16 {" L32A "," L32B "}, {%64,%65,%66,%67}, %68, p, 1, 1, %70;\n}"
                 : R64(d, 0) : "r"(a0), "r"(a1), "r"(a2), "r"(a3), "l"(db), "r"(acc), "n"(TB));
}
template <int TB> __device__ __forceinline__ void wgmma_ss256(float (&d)[128], uint64_t da, uint64_t db, int acc) {
    asm volatile("{\n.reg .pred p;\nsetp.ne.b32 p, %130, 0;\n"
                 "wgmma.mma_async.sync.aligned.m64n256k16.f32.bf16.bf16 {" L32A "," L32B "," L32C "," L32D "}, %128, %129, p, 1, 1, 0, %131;\n}"
                 : R64(d, 0), R64(d, 64) : "l"(da), "l"(db), "r"(acc), "n"(TB));
}
template <int N> __device__ __forceinline__ void zero_acc(float (&d)[N]) {
#pragma unroll
    for (int i = 0; i < N; i++) d[i] = 0.f;
}
__device__ __forceinline__ void pin64(float (&d)[64]) { asm volatile("" : R64(d, 0)::"memory"); }
__device__ __forceinline__ void pin128(float (&d)[128]) { asm volatile("" : R64(d, 0), R64(d, 64)::"memory"); }

struct Ring {
    uint32_t slot, phase;
    __device__ __forceinline__ void advance() {
        if (++slot == NSLOT) { slot = 0; phase ^= 1; }
    }
};

struct Consumer {
    uint32_t sbase;
    uint32_t stg;
    uint32_t stm_addr;
    uint32_t nstores;
    int wg, tid;
    Ring ring;

    __device__ __forceinline__ uint32_t bars() const { return sbase + BAR_OFF; }
    __device__ __forceinline__ uint32_t acquire() {
        mbar_wait(bars() + BAR_FULL + ring.slot * 8, ring.phase);
        uint32_t s = ring.slot;
        ring.advance();
        return s;
    }
    __device__ __forceinline__ void release(uint32_t s) const {
        if (tid < 2) mbar_arrive_cta(bars() + BAR_EMPTY + s * 8, tid);
    }
    __device__ __forceinline__ uint32_t slot_addr(uint32_t s) const { return sbase + s * SLOT_BYTES; }
    __device__ __forceinline__ void stg_wait() const { mbar_wait(bars() + BAR_STG_EMPTY + wg * 8, (nstores & 1) ^ 1); }
    __device__ __forceinline__ void stg_write(const uint32_t* pk) const {
#pragma unroll
        for (int i = 0; i < 8; i++)
            stmatrix_x4((stm_addr ^ ((i & 3) * 32)) + (i >> 2) * 8192, pk[4 * i], pk[4 * i + 1], pk[4 * i + 2], pk[4 * i + 3]);
        fence_async_smem();
    }
    __device__ __forceinline__ void stg_submit() {
        mbar_arrive(bars() + BAR_STG_FULL + wg * 8);
        nstores++;
    }
};

__device__ __forceinline__ void gemm_mainloop(Consumer& c, float (&acc)[128], int npairs) {
    uint32_t pa = 0, pb = 0;
    zero_acc(acc);
#pragma unroll 1
    for (int p = 0; p < npairs; p++) {
        uint32_t s0 = c.acquire();
        uint32_t s1 = c.acquire();
        uint32_t a = c.slot_addr(s1) + c.wg * 8192;
        uint32_t b = c.slot_addr(s0);
        wg_fence();
#pragma unroll
        for (int kk = 0; kk < 4; kk++) wgmma_ss256<1>(acc, desc_kmajor(a + kk * 32), desc_nmajor(b + kk * 2048, 8192), 1);
        wg_commit();
        wg_wait<1>();
        if (p > 0) { c.release(pa); c.release(pb); }
        uint32_t s2 = c.acquire();
        b = c.slot_addr(s2);
        wg_fence();
#pragma unroll
        for (int kk = 0; kk < 4; kk++) wgmma_ss256<1>(acc, desc_kmajor(a + 16384 + kk * 32), desc_nmajor(b + kk * 2048, 8192), 1);
        wg_commit();
        wg_wait<1>();
        c.release(s0);
        pa = s1;
        pb = s2;
    }
    wg_wait<0>();
    pin128(acc);
    c.release(pa);
    c.release(pb);
}

__device__ __forceinline__ void store_tile256(Consumer& c, const uint32_t (&pk)[64]) {
    c.stg_wait();
    c.stg_write(pk);
    c.stg_submit();
    c.stg_wait();
    c.stg_write(pk + 32);
    c.stg_submit();
}

__device__ __forceinline__ float quad_max(float x) {
    x = fmaxf(x, __shfl_xor_sync(0xffffffffu, x, 1));
    return fmaxf(x, __shfl_xor_sync(0xffffffffu, x, 2));
}
__device__ __forceinline__ float quad_sum(float x) {
    x += __shfl_xor_sync(0xffffffffu, x, 1);
    return x + __shfl_xor_sync(0xffffffffu, x, 2);
}
__device__ __forceinline__ void feature_map(const float* x, const __nv_bfloat16* wphi_h, int lane, uint32_t (&phi)[4][2]) {
    constexpr float LOG2E = 1.4426950408889634f;
    const uint32_t* w = reinterpret_cast<const uint32_t*>(wphi_h) + (lane >> 2) * 8 + (lane & 3);
    uint32_t w00 = movmatrix(__ldg(w)), w01 = movmatrix(__ldg(w + 64));
    uint32_t w10 = movmatrix(__ldg(w + 4)), w11 = movmatrix(__ldg(w + 68));
    uint32_t a0 = pack_bf16(x[0], x[1]), a1 = pack_bf16(x[2], x[3]), a2 = pack_bf16(x[4], x[5]), a3 = pack_bf16(x[6], x[7]);
    float p0[4] = {0.f, 0.f, 0.f, 0.f}, p1[4] = {0.f, 0.f, 0.f, 0.f};
    mma16816(p0, a0, a1, a2, a3, w00, w01);
    mma16816(p1, a0, a1, a2, a3, w10, w11);
#pragma unroll
    for (int r = 0; r < 2; r++) {
        float v0 = round_bf16(p0[2 * r]), v1 = round_bf16(p0[2 * r + 1]), v2 = round_bf16(p1[2 * r]), v3 = round_bf16(p1[2 * r + 1]);
        float mx = quad_max(fmaxf(fmaxf(v0, v1), fmaxf(v2, v3)));
        float mn = -quad_max(-fminf(fminf(v0, v1), fminf(v2, v3)));
        float e0 = ex2((v0 - mx) * LOG2E), e1 = ex2((v1 - mx) * LOG2E), e2 = ex2((v2 - mx) * LOG2E), e3 = ex2((v3 - mx) * LOG2E);
        float n0 = ex2((mn - v0) * LOG2E), n1 = ex2((mn - v1) * LOG2E), n2 = ex2((mn - v2) * LOG2E), n3 = ex2((mn - v3) * LOG2E);
        float ip = __fdividef(1.f, quad_sum((e0 + e1) + (e2 + e3)));
        float in = __fdividef(1.f, quad_sum((n0 + n1) + (n2 + n3)));
        phi[0][r] = pack_bf16(e0 * ip, e1 * ip);
        phi[1][r] = pack_bf16(e2 * ip, e3 * ip);
        phi[2][r] = pack_bf16(n0 * in, n1 * in);
        phi[3][r] = pack_bf16(n2 * in, n3 * in);
    }
}

__device__ __forceinline__ void red_add2(float* p, float a, float b) {
    asm volatile("red.global.add.v2.f32 [%0], {%1, %2};" ::"l"(p), "f"(a), "f"(b) : "memory");
}
__device__ __forceinline__ uint32_t ld_pack2(const float* p) {
    float2 v = __ldcg(reinterpret_cast<const float2*>(p));
    return pack_bf16(v.x, v.y);
}

__device__ __forceinline__ void a1_epilogue(const float (&acc)[128], const __nv_bfloat16* wphi, float* akv, int hg, int lane) {
#pragma unroll
    for (int hh = 0; hh < 8; hh++) {
        int head = hg * 8 + hh;
        uint32_t phi[4][2];
        feature_map(&acc[8 * hh], wphi + head * 256, lane, phi);
        const float* v = &acc[64 + 8 * hh];
        uint32_t a0 = movmatrix(pack_bf16(v[0], v[1])), a1 = movmatrix(pack_bf16(v[4], v[5]));
        uint32_t a2 = movmatrix(pack_bf16(v[2], v[3])), a3 = movmatrix(pack_bf16(v[6], v[7]));
        float* dst = akv + head * (17 * 32) + (lane >> 2) * 32 + (lane & 3) * 2;
#pragma unroll
        for (int t = 0; t < 4; t++) {
            uint32_t b0 = movmatrix(phi[t][0]), b1 = movmatrix(phi[t][1]);
            float kv[4] = {0.f, 0.f, 0.f, 0.f}, z[4] = {0.f, 0.f, 0.f, 0.f};
            mma16816(kv, a0, a1, a2, a3, b0, b1);
            mma16816(z, 0x3F803F80u, 0x3F803F80u, 0x3F803F80u, 0x3F803F80u, b0, b1);
            red_add2(dst + 8 * t, kv[0], kv[1]);
            red_add2(dst + 8 * t + 8 * 32, kv[2], kv[3]);
            if (lane < 4) red_add2(dst + 8 * t + 16 * 32, z[0], z[1]);
        }
    }
}

__device__ __forceinline__ void a2_epilogue(const float (&acc)[128], uint32_t (&pk)[64], const __nv_bfloat16* wphi, const float* akv, int nh, int lane) {
#pragma unroll
    for (int hh = 0; hh < 16; hh++) {
        int head = nh * 16 + hh;
        uint32_t phi[4][2];
        feature_map(&acc[8 * hh], wphi + head * 256, lane, phi);
        const float* kv = akv + head * (17 * 32) + (lane >> 2) * 32 + (lane & 3) * 2;
        const float* zp = akv + head * (17 * 32) + 16 * 32 + (lane & 3) * 2;
        float n0[4] = {0.f, 0.f, 0.f, 0.f}, n1[4] = {0.f, 0.f, 0.f, 0.f}, dn[4] = {0.f, 0.f, 0.f, 0.f};
#pragma unroll
        for (int s = 0; s < 2; s++) {
            uint32_t a0 = phi[2 * s][0], a1 = phi[2 * s][1], a2 = phi[2 * s + 1][0], a3 = phi[2 * s + 1][1];
            mma16816(n0, a0, a1, a2, a3, ld_pack2(kv + 16 * s), ld_pack2(kv + 16 * s + 8));
            mma16816(n1, a0, a1, a2, a3, ld_pack2(kv + 256 + 16 * s), ld_pack2(kv + 256 + 16 * s + 8));
            mma16816(dn, a0, a1, a2, a3, ld_pack2(zp + 16 * s), ld_pack2(zp + 16 * s + 8));
        }
        float d0 = __fdividef(1.f, round_bf16(round_bf16(dn[0]) + 1e-6f)), d1 = __fdividef(1.f, round_bf16(round_bf16(dn[2]) + 1e-6f));
        pk[4 * hh + 0] = pack_bf16(round_bf16(n0[0]) * d0, round_bf16(n0[1]) * d0);
        pk[4 * hh + 1] = pack_bf16(round_bf16(n0[2]) * d1, round_bf16(n0[3]) * d1);
        pk[4 * hh + 2] = pack_bf16(round_bf16(n1[0]) * d0, round_bf16(n1[1]) * d0);
        pk[4 * hh + 3] = pack_bf16(round_bf16(n1[2]) * d1, round_bf16(n1[3]) * d1);
    }
}

constexpr float SM_SCALE_LOG2 = 0.08838834764831845f * 1.4426950408889634f;

template <bool FIRST>
__device__ __forceinline__ void softmax_block(float (&s)[64], float (&m)[2], float (&l)[2], float (&alpha)[2]) {
#pragma unroll
    for (int r = 0; r < 2; r++) {
        float t0 = fmaxf(s[2 * r], s[2 * r + 1]), t1 = fmaxf(s[4 + 2 * r], s[5 + 2 * r]);
        float t2 = fmaxf(s[8 + 2 * r], s[9 + 2 * r]), t3 = fmaxf(s[12 + 2 * r], s[13 + 2 * r]);
#pragma unroll
        for (int i = 4; i < 16; i += 4) {
            t0 = fmaxf(t0, fmaxf(s[4 * i + 2 * r], s[4 * i + 2 * r + 1]));
            t1 = fmaxf(t1, fmaxf(s[4 * i + 4 + 2 * r], s[4 * i + 5 + 2 * r]));
            t2 = fmaxf(t2, fmaxf(s[4 * i + 8 + 2 * r], s[4 * i + 9 + 2 * r]));
            t3 = fmaxf(t3, fmaxf(s[4 * i + 12 + 2 * r], s[4 * i + 13 + 2 * r]));
        }
        float mx = quad_max(fmaxf(fmaxf(t0, t1), fmaxf(t2, t3)));
        if (FIRST) {
            m[r] = mx;
        } else {
            mx = fmaxf(mx, m[r]);
            alpha[r] = ex2((m[r] - mx) * SM_SCALE_LOG2);
            m[r] = mx;
        }
    }
    float mc0 = -m[0] * SM_SCALE_LOG2, mc1 = -m[1] * SM_SCALE_LOG2;
    float a0 = 0.f, a1 = 0.f, b0 = 0.f, b1 = 0.f;
#pragma unroll
    for (int i = 0; i < 16; i++) {
        s[4 * i] = ex2(fmaf(s[4 * i], SM_SCALE_LOG2, mc0));
        s[4 * i + 1] = ex2(fmaf(s[4 * i + 1], SM_SCALE_LOG2, mc0));
        s[4 * i + 2] = ex2(fmaf(s[4 * i + 2], SM_SCALE_LOG2, mc1));
        s[4 * i + 3] = ex2(fmaf(s[4 * i + 3], SM_SCALE_LOG2, mc1));
        a0 += s[4 * i];
        a1 += s[4 * i + 1];
        b0 += s[4 * i + 2];
        b1 += s[4 * i + 3];
    }
    if (FIRST) {
        l[0] = a0 + a1;
        l[1] = b0 + b1;
    } else {
        l[0] = fmaf(l[0], alpha[0], a0 + a1);
        l[1] = fmaf(l[1], alpha[1], b0 + b1);
    }
}

__device__ __forceinline__ void issue_qk(float (&s)[64], uint32_t q, uint32_t k) {
#pragma unroll
    for (int kk = 0; kk < 8; kk++)
        wgmma_ss128<0>(s, desc_kmajor(q + (kk >> 2) * 8192 + (kk & 3) * 32), desc_kmajor(k + (kk >> 2) * 16384 + (kk & 3) * 32), kk);
    wg_commit();
}
__device__ __forceinline__ void issue_pv(float (&o)[64], const uint32_t (&p)[32], uint32_t v) {
#pragma unroll
    for (int kk = 0; kk < 8; kk++)
        wgmma_rs128<1>(o, p[4 * kk], p[4 * kk + 1], p[4 * kk + 2], p[4 * kk + 3], desc_nmajor(v + kk * 2048, 16384), 1);
    wg_commit();
}
__device__ __forceinline__ void pack64(const float (&s)[64], uint32_t (&p)[32]) {
#pragma unroll
    for (int i = 0; i < 32; i++) p[i] = pack_bf16(s[2 * i], s[2 * i + 1]);
}

__device__ __forceinline__ void attention_item(Consumer& c, int j, int rank) {
    float s[64], o[64];
    uint32_t p[32];
    const int lane = c.tid & 31, warp = c.tid >> 5;
    {
        uint32_t prev = 0;
        zero_acc(s);
#pragma unroll 1
        for (int ch = 0; ch < 8; ch++) {
            uint32_t sl = c.acquire();
            uint32_t a = c.slot_addr(sl) + c.wg * 8192, b = c.slot_addr(sl) + 16384;
            wg_fence();
#pragma unroll
            for (int kk = 0; kk < 4; kk++) wgmma_ss128<1>(s, desc_kmajor(a + kk * 32), desc_nmajor(b + kk * 2048, 8192), 1);
            wg_commit();
            wg_wait<1>();
            if (ch > 0) c.release(prev);
            prev = sl;
        }
        wg_wait<0>();
        pin64(s);
        c.release(prev);
        pack64(s, p);
        c.stg_wait();
        c.stg_write(p);
        bar_sync(3 + c.wg, 128);
    }
    const bool lead = c.wg == 1;
    const int nblk = 2 * j + 1 + c.wg;
    float m[2], l[2], alpha[2];
    {
        if (!lead) c.release(c.acquire());
        uint32_t sk = c.acquire();
        if (!lead) bar_sync(1, 256);
        wg_fence();
        issue_qk(s, c.stg, c.slot_addr(sk));
        if (!lead) bar_arrive(2, 256);
        wg_wait<0>();
        pin64(s);
        c.release(sk);
        const int lim = warp * 16 + (lane >> 2) + ((c.wg ^ rank) ? 64 : 0) - (lane & 3) * 2;
#pragma unroll
        for (int i = 0; i < 16; i++) {
            if (8 * i > lim) s[4 * i] = -INFINITY;
            if (8 * i + 1 > lim) s[4 * i + 1] = -INFINITY;
            if (8 * i > lim + 8) s[4 * i + 2] = -INFINITY;
            if (8 * i + 1 > lim + 8) s[4 * i + 3] = -INFINITY;
        }
        softmax_block<true>(s, m, l, alpha);
        pack64(s, p);
        if (!lead) c.release(c.acquire());
    }
    zero_acc(o);
#pragma unroll 1
    for (int i = 1; i < nblk; i++) {
        uint32_t sk = c.acquire();
        uint32_t sv = c.acquire();
        if (!lead || i > 1) bar_sync(1 + c.wg, 256);
        wg_fence();
        issue_qk(s, c.stg, c.slot_addr(sk));
        issue_pv(o, p, c.slot_addr(sv));
        bar_arrive(2 - c.wg, 256);
        wg_wait<1>();
        pin64(s);
        c.release(sk);
        softmax_block<false>(s, m, l, alpha);
        wg_wait<0>();
        pin64(o);
        c.release(sv);
#pragma unroll
        for (int t = 0; t < 16; t++) {
            o[4 * t] *= alpha[0];
            o[4 * t + 1] *= alpha[0];
            o[4 * t + 2] *= alpha[1];
            o[4 * t + 3] *= alpha[1];
        }
        pack64(s, p);
    }
    {
        uint32_t sv = c.acquire();
        bar_sync(1 + c.wg, 256);
        wg_fence();
        issue_pv(o, p, c.slot_addr(sv));
        if (lead) bar_arrive(1, 256);
        float i0 = __fdividef(1.f, quad_sum(l[0])), i1 = __fdividef(1.f, quad_sum(l[1]));
        wg_wait<0>();
        pin64(o);
        c.release(sv);
#pragma unroll
        for (int t = 0; t < 16; t++) {
            p[2 * t] = pack_bf16(o[4 * t] * i0, o[4 * t + 1] * i0);
            p[2 * t + 1] = pack_bf16(o[4 * t + 2] * i1, o[4 * t + 3] * i1);
        }
        c.stg_write(p);
        c.stg_submit();
    }
}

struct Producer {
    uint32_t sbase;
    Ring ring;
    __device__ __forceinline__ uint32_t full() const { return sbase + BAR_OFF + BAR_FULL + ring.slot * 8; }
    __device__ __forceinline__ uint32_t begin() {
        mbar_wait(sbase + BAR_OFF + BAR_EMPTY + ring.slot * 8, ring.phase ^ 1);
        mbar_expect(full(), SLOT_BYTES);
        return sbase + ring.slot * SLOT_BYTES;
    }
    __device__ __forceinline__ void load_b(const CUtensorMap* tm, int col, int krow, int rank) {
        uint32_t dst = begin() + rank * 16384;
        tma_2d_mc(dst, tm, col, krow, full());
        tma_2d_mc(dst + 8192, tm, col + 64, krow, full());
        ring.advance();
    }
    __device__ __forceinline__ void load_a_map(const CUtensorMap* tm, int k, int row) {
        uint32_t dst = begin();
        tma_2d(dst, tm, k, row, full());
        tma_2d(dst + 16384, tm, k + 64, row, full());
        ring.advance();
    }
    __device__ __forceinline__ void load_a_img(const uint8_t* img) {
        uint32_t dst = begin();
        bulk_load(dst, img, 16384, full());
        bulk_load(dst + 16384, img + 16384, 16384, full());
        ring.advance();
    }
    __device__ __forceinline__ void load_kv(const uint8_t* img, int rank) {
        uint32_t dst = begin();
        bulk_load_mc(dst + rank * 16384, img + rank * 16384, 16384, full());
        ring.advance();
    }
};

__device__ __forceinline__ int strip_of(int rank, int wg) { return rank == 0 ? 3 * wg : 1 + wg; }

__global__ void __cluster_dims__(2, 1, 1) __launch_bounds__(384, 1) fused_kernel(const __grid_constant__ Params P) {
    extern __shared__ uint8_t smem_raw[];
    const uint32_t sbase = (smem_u32(smem_raw) + 1023) & ~1023u;
    const uint32_t bars = sbase + BAR_OFF;
    const int warp = __shfl_sync(0xffffffffu, threadIdx.x >> 5, 0), lane = threadIdx.x & 31;
    const int rank = blockIdx.x & 1, cluster = blockIdx.x >> 1;
    const uint32_t epoch = g_epoch[blockIdx.x];

    if (threadIdx.x == 0) {
        for (int i = 0; i < NSLOT; i++) {
            mbar_init(bars + BAR_FULL + i * 8, 1);
            mbar_init(bars + BAR_EMPTY + i * 8, 4);
        }
        for (int i = 0; i < 2; i++) {
            mbar_init(bars + BAR_STG_FULL + i * 8, 128);
            mbar_init(bars + BAR_STG_EMPTY + i * 8, 1);
        }
        asm volatile("fence.mbarrier_init.release.cluster;" ::: "memory");
    }
    __syncthreads();
    cluster_sync();

    if (warp >= 8) {
        asm volatile("setmaxnreg.dec.sync.aligned.u32 40;");
        if (warp == 8) {
            Producer pr{sbase, {0, 0}};
#pragma unroll 1
            for (int it = 0; it < MAX_ITEMS; it++) {
                const uint32_t item = P.sched[cluster][it];
                const int type = item >> 8, a = (item >> 3) & 31, j = item & 7;
                if (type == T_END) break;
                const int tile = 2 * j + rank;
                if (type == T_ATT) {
                    if (lane == 0) {
                        const int r0 = 256 * j + 64 * strip_of(rank, 0), r1 = 256 * j + 64 * strip_of(rank, 1);
#pragma unroll 1
                        for (int ch = 0; ch < 8; ch++) {
                            uint32_t dst = pr.begin();
                            tma_2d(dst, &P.tm_xb64, 64 * ch, r0, pr.full());
                            tma_2d(dst + 8192, &P.tm_xb64, 64 * ch, r1, pr.full());
                            tma_2d_mc(dst + 16384 + rank * 8192, &P.tm_wq, 128 * a + 64 * rank, 64 * ch, pr.full());
                            pr.ring.advance();
                        }
                    }
                    __syncwarp();
                    if (lane <= j) flag_wait(&g_flags[F_KV + a * 8 + lane], (epoch + 1) * 4);
                    __syncwarp();
                    if (lane == 0) {
                        fence_async_global();
                        const uint8_t* kimg = g_K + (size_t)a * 16 * SLOT_BYTES;
                        const uint8_t* vimg = g_V + (size_t)a * 16 * SLOT_BYTES;
                        pr.load_kv(kimg + (2 * j + 1) * SLOT_BYTES, rank);
#pragma unroll 1
                        for (int n = 2 * j; n >= 0; n--) {
                            pr.load_kv(kimg + n * SLOT_BYTES, rank);
                            pr.load_kv(vimg + (n + 1) * SLOT_BYTES, rank);
                        }
                        pr.load_kv(vimg, rank);
                    }
                } else if (type == T_OP) {
                    int ready = 0;
#pragma unroll 1
                    for (int h = 0; h < 32; h++) {
                        if (h >= ready) {
                            uint32_t n = 0;
                            while (true) {
                                bool ok = (int32_t)(ld_acquire(&g_flags[F_CTX + j * 32 + lane]) - (epoch + 1) * 4) >= 0;
                                uint32_t miss = ~__ballot_sync(0xffffffffu, ok);
                                ready = miss ? __ffs(miss) - 1 : 32;
                                if (ready > h) break;
                                if (++n > SPIN_LIMIT) { abort_launch(); break; }
                                __nanosleep(64);
                            }
                            if (lane == 0) fence_async_global();
                        }
                        if (lane == 0) {
                            pr.load_b(&P.tm_wo, 256 * a + 128 * rank, 128 * h, rank);
                            pr.load_a_img(g_ctx + (size_t)(tile * 32 + h) * SLOT_BYTES);
                            pr.load_b(&P.tm_wo, 256 * a + 128 * rank, 128 * h + 64, rank);
                        }
                        __syncwarp();
                    }
                } else if (lane == 0) {
                    const CUtensorMap* tb;
                    int col;
                    if (type == T_KV) { tb = rank ? &P.tm_wuv : &P.tm_wuk; col = 128 * a; }
                    else if (type == T_A1) { tb = &P.tm_awqkv; col = 512 + 512 * rank + 128 * a; }
                    else if (type == T_A2) { tb = &P.tm_awqkv; col = 256 * a + 128 * rank; }
                    else { tb = &P.tm_awo; col = 256 * a + 128 * rank; }
                    if (type == T_A3) {
                        flag_wait(&g_flags[F_O + j], (epoch + 1) * 8);
                        fence_async_global();
                    }
#pragma unroll 1
                    for (int p = 0; p < 4; p++) {
                        pr.load_b(tb, col, 128 * p, rank);
                        if (type == T_A3) pr.load_a_img(g_o + (size_t)(tile * 4 + p) * SLOT_BYTES);
                        else pr.load_a_map(type == T_KV ? &P.tm_ckv : &P.tm_xa, 128 * p, 128 * tile);
                        pr.load_b(tb, col, 128 * p + 64, rank);
                    }
                }
                __syncwarp();
            }
        } else if (warp < 11) {
            if (lane == 0) {
                const int wg = warp - 9;
                const uint32_t stg = sbase + STG_OFF + wg * 16384;
                uint32_t n = 0;
#pragma unroll 1
                for (int it = 0; it < MAX_ITEMS; it++) {
                    const uint32_t item = P.sched[cluster][it];
                    const int type = item >> 8, a = (item >> 3) & 31, j = item & 7;
                    if (type == T_END) break;
                    if (type == T_A1) continue;
                    const int tile = 2 * j + rank;
                    const int rounds = type == T_ATT ? 1 : 2;
#pragma unroll 1
                    for (int r = 0; r < rounds; r++) {
                        mbar_wait(bars + BAR_STG_FULL + wg * 8, n & 1);
                        n++;
                        if (type == T_OP || type == T_A3) {
                            const int col = (type == T_OP ? 512 : 0) + 256 * a + 128 * r, row = 128 * tile + 64 * wg;
                            tma_store_2d(&P.tm_out, col, row, stg);
                            tma_store_2d(&P.tm_out, col + 64, row, stg + 8192);
                        } else {
                            uint8_t* dst;
                            if (type == T_KV) dst = (r ? g_V : g_K) + (size_t)(a * 16 + tile) * SLOT_BYTES + wg * 8192;
                            else if (type == T_A2) dst = g_o + (size_t)(tile * 4 + 2 * a + r) * SLOT_BYTES + wg * 8192;
                            else {
                                const int st = strip_of(rank, wg);
                                dst = g_ctx + (size_t)((2 * j + (st >> 1)) * 32 + a) * SLOT_BYTES + (st & 1) * 8192;
                            }
                            bulk_store(dst, stg, 8192);
                            bulk_store(dst + 16384, stg + 8192, 8192);
                        }
                        bulk_commit();
                        bulk_wait_read();
                        mbar_arrive(bars + BAR_STG_EMPTY + wg * 8);
                    }
                    if (type == T_KV || type == T_ATT || type == T_A2) {
                        bulk_wait_all();
                        flag_signal(&g_flags[type == T_KV ? F_KV + a * 8 + j : type == T_ATT ? F_CTX + j * 32 + a : F_O + j]);
                    }
                }
                bulk_wait_all();
            }
        } else {
            float4* z = reinterpret_cast<float4*>(g_akv[(epoch + 1) & 1]);
            for (int i = blockIdx.x * 32 + lane; i < 32 * 17 * 32 / 4; i += gridDim.x * 32) z[i] = make_float4(0.f, 0.f, 0.f, 0.f);
            if (lane == 0) g_epoch[blockIdx.x] = epoch + 1;
        }
        __syncwarp();
        cluster_sync();
    } else {
        asm volatile("setmaxnreg.inc.sync.aligned.u32 232;");
        Consumer c;
        c.sbase = sbase;
        c.wg = warp >> 2;
        c.tid = threadIdx.x & 127;
        c.stg = sbase + STG_OFF + c.wg * 16384;
        {
            const int row = (warp & 3) * 16 + ((lane >> 3) & 1) * 8 + (lane & 7);
            c.stm_addr = c.stg + row * 128 + (((lane >> 4) ^ (lane & 7)) * 16);
        }
        c.nstores = 0;
        c.ring = {0, 0};
#pragma unroll 1
        for (int it = 0; it < MAX_ITEMS; it++) {
            const uint32_t item = P.sched[cluster][it];
            const int type = item >> 8, a = (item >> 3) & 31, j = item & 7;
            if (type == T_END) break;
            if (type == T_ATT) {
                attention_item(c, j, rank);
            } else {
                float acc[128];
                gemm_mainloop(c, acc, type == T_OP ? 32 : 4);
                float* akv = g_akv[epoch & 1];
                if (type == T_A1) {
                    a1_epilogue(acc, P.w_phi, akv, a, lane);
                    __threadfence();
                    bar_sync(3 + c.wg, 128);
                    if (c.tid == 0) flag_signal(&g_flags[F_AKV + a]);
                } else {
                    uint32_t pk[64];
                    if (type == T_A2) {
                        flag_wait(&g_flags[F_AKV + 2 * a + (lane & 1)], (epoch + 1) * 32);
                        __syncwarp();
                        a2_epilogue(acc, pk, P.w_phi, akv, a, lane);
                    } else {
#pragma unroll
                        for (int i = 0; i < 64; i++) pk[i] = pack_bf16(acc[2 * i], acc[2 * i + 1]);
                    }
                    store_tile256(c, pk);
                }
            }
        }
        cluster_sync();
    }
}

typedef CUresult (*EncodeFn)(CUtensorMap*, CUtensorMapDataType, cuuint32_t, void*, const cuuint64_t*, const cuuint64_t*,
                             const cuuint32_t*, const cuuint32_t*, CUtensorMapInterleave, CUtensorMapSwizzle,
                             CUtensorMapL2promotion, CUtensorMapFloatOOBfill);

void make_map(EncodeFn fn, CUtensorMap* tm, const void* ptr, int rows, int cols, int box_rows) {
    cuuint64_t dims[2] = {(cuuint64_t)cols, (cuuint64_t)rows};
    cuuint64_t strides[1] = {(cuuint64_t)cols * 2};
    cuuint32_t box[2] = {64, (cuuint32_t)box_rows};
    cuuint32_t estr[2] = {1, 1};
    fn(tm, CU_TENSOR_MAP_DATA_TYPE_BFLOAT16, 2, const_cast<void*>(ptr), dims, strides, box, estr, CU_TENSOR_MAP_INTERLEAVE_NONE,
       CU_TENSOR_MAP_SWIZZLE_128B, CU_TENSOR_MAP_L2_PROMOTION_L2_256B, CU_TENSOR_MAP_FLOAT_OOB_FILL_NONE);
}

inline uint16_t enc(int type, int a, int j) { return (uint16_t)((type << 8) | (a << 3) | j); }

void build_schedule(uint16_t (*sched)[MAX_ITEMS], int ncl) {
    static uint16_t order[640];
    int n = 0;
    for (int h = 0; h < 8; h++) for (int j = 0; j < 8; j++) order[n++] = enc(T_KV, h, j);
    for (int g = 0; g < 4; g++) {
        if (g < 3) for (int h = 8 * g + 8; h < 8 * g + 16; h++) for (int j = 0; j < 8; j++) order[n++] = enc(T_KV, h, j);
        if (g == 0) for (int a = 0; a < 4; a++) for (int j = 0; j < 8; j++) order[n++] = enc(T_A1, a, j);
        if (g == 1) for (int a = 0; a < 2; a++) for (int j = 0; j < 8; j++) order[n++] = enc(T_A2, a, j);
        if (g == 2) for (int a = 0; a < 2; a++) for (int j = 0; j < 8; j++) order[n++] = enc(T_A3, a, j);
        for (int j = 7; j >= 0; j--) for (int h = 8 * g; h < 8 * g + 8; h++) order[n++] = enc(T_ATT, h, j);
    }
    float t[MAX_CLUSTERS];
    int cnt[MAX_CLUSTERS];
    for (int c = 0; c < MAX_CLUSTERS; c++) {
        t[c] = c < 16 ? 66.f : 0.f;
        cnt[c] = 0;
        for (int i = 0; i < MAX_ITEMS; i++) sched[c][i] = enc(T_END, 0, 0);
    }
    float busy[MAX_CLUSTERS];
    for (int c = 0; c < MAX_CLUSTERS; c++) busy[c] = 0.f;
    const float horizon = (5248.f + 2048.f + 512.f + 1024.f + 300.f) / ncl;
    for (int i = 0; i < n; i++) {
        int type = order[i] >> 8, j = order[i] & 7;
        float cost = type == T_ATT ? 4.f * j + 7.5f : 8.5f;
        int best = -1;
        for (int c = 0; c < ncl; c++) {
            if (cnt[c] >= MAX_ITEMS - 2) continue;
            if (c < 16 && busy[c] + cost + t[c] > horizon) continue;
            if (best < 0 || busy[c] < busy[best]) best = c;
        }
        sched[best][cnt[best]++] = order[i];
        busy[best] += cost;
    }
    for (int c = 0; c < 16; c++) sched[c][cnt[c]++] = enc(T_OP, c & 1, c >> 1);
}

}

extern "C" void kernel_launch(void* const* d_in, const int* in_sizes, int n_in, void* d_out, int out_size) {
    static Params P;
    static bool ready = false;
    if (!ready) {
        void* fp = nullptr;
        cudaDriverEntryPointQueryResult qr;
        cudaGetDriverEntryPoint("cuTensorMapEncodeTiled", &fp, cudaEnableDefault, &qr);
        EncodeFn fn = (EncodeFn)fp;
        make_map(fn, &P.tm_xa, d_in[0], 2048, 512, 128);
        make_map(fn, &P.tm_awqkv, d_in[1], 512, 1536, 64);
        P.w_phi = (const __nv_bfloat16*)d_in[2];
        make_map(fn, &P.tm_awo, d_in[3], 512, 512, 64);
        make_map(fn, &P.tm_xb64, d_in[4], 2048, 512, 64);
        make_map(fn, &P.tm_ckv, d_in[5], 2048, 512, 128);
        make_map(fn, &P.tm_wq, d_in[6], 512, 4096, 64);
        make_map(fn, &P.tm_wuk, d_in[7], 512, 4096, 64);
        make_map(fn, &P.tm_wuv, d_in[8], 512, 4096, 64);
        make_map(fn, &P.tm_wo, d_in[9], 4096, 512, 64);
        make_map(fn, &P.tm_out, d_out, 2048, 1024, 64);
        build_schedule(P.sched, MAX_CLUSTERS);
        cudaFuncSetAttribute(fused_kernel, cudaFuncAttributeMaxDynamicSharedMemorySize, SMEM_BYTES);
        ready = true;
    }
    fused_kernel<<<2 * MAX_CLUSTERS, 384, SMEM_BYTES>>>(P);
}
```

```cpp
#include <cuda_runtime.h>
#include <cuda_bf16.h>
#include <cuda.h>
#include <stdint.h>
#include <string.h>

namespace {

constexpr int NSLOT = 6;
constexpr int SLOT_BYTES = 32768;
constexpr int STG_OFF = NSLOT * SLOT_BYTES;
constexpr int BAR_OFF = STG_OFF + 32768;
constexpr int SMEM_BYTES = BAR_OFF + 256 + 1024;
constexpr int MAX_CLUSTERS = 66;
constexpr int MAX_ITEMS = 16;
constexpr uint32_t SPIN_LIMIT = 1u << 20;

constexpr int BAR_FULL = 0;
constexpr int BAR_EMPTY = 64;
constexpr int BAR_STG_FULL = 128;
constexpr int BAR_STG_EMPTY = 144;
constexpr int BAR_STG2_FULL = 160;
constexpr int EPOCH_WORD = 184;
constexpr int DEP_TICKET = 176;

enum { T_KV = 0, T_ATT = 1, T_OP = 2, T_A1 = 3, T_A2 = 4, T_A3 = 5, T_END = 7 };

constexpr int F_KV = 0;
constexpr int F_CTX = 256;
constexpr int F_AKV = 512;
constexpr int F_O = 544;
constexpr int F_ZERO = 576;
constexpr int F_TOTAL = 608;

constexpr int AKV_ROW = 40;
constexpr int AKV_HEAD = 17 * AKV_ROW;
constexpr int TAB_W_OFF = 8 * AKV_HEAD * 4;

struct Params {
    CUtensorMap tm_xb64;
    CUtensorMap tm_ckv;
    CUtensorMap tm_xa;
    CUtensorMap tm_wq, tm_wuk, tm_wuv, tm_wo, tm_awqkv, tm_awo;
    CUtensorMap tm_out;
    const __nv_bfloat16* w_phi;
    uint8_t* out;
    uint16_t items[MAX_CLUSTERS][MAX_ITEMS];
    uint8_t op_order[8][32];
};

__device__ __align__(1024) uint8_t g_K[32 * 16 * SLOT_BYTES];
__device__ __align__(1024) uint8_t g_V[32 * 16 * SLOT_BYTES];
__device__ __align__(1024) uint8_t g_ctx[16 * 32 * SLOT_BYTES];
__device__ __align__(1024) uint8_t g_o[16 * 4 * SLOT_BYTES];
__device__ __align__(1024) float g_akv[2][32 * AKV_HEAD];
__device__ uint32_t g_flags[F_TOTAL];
__device__ uint32_t g_epoch[2 * MAX_CLUSTERS];
#define TR(c, idx)

__device__ __forceinline__ uint32_t smem_u32(const void* p) { return (uint32_t)__cvta_generic_to_shared(p); }
__device__ __forceinline__ void abort_launch() { asm volatile("st.global.u32 [%0], %1;" ::"l"(0ull), "r"(0) : "memory"); }
__device__ __forceinline__ void mbar_init(uint32_t a, uint32_t c) {
    asm volatile("mbarrier.init.shared::cta.b64 [%0], %1;" ::"r"(a), "r"(c) : "memory");
}
__device__ __forceinline__ bool mbar_try(uint32_t a, uint32_t ph) {
    uint32_t ok;
    asm volatile("{\n.reg .pred p;\nmbarrier.try_wait.parity.shared::cta.b64 p, [%1], %2;\nselp.u32 %0, 1, 0, p;\n}"
                 : "=r"(ok) : "r"(a), "r"(ph) : "memory");
    return ok;
}
__device__ __forceinline__ void mbar_wait(uint32_t a, uint32_t ph) {
    uint32_t n = 0;
#pragma unroll 1
    while (!mbar_try(a, ph)) {
        if (++n > SPIN_LIMIT) { abort_launch(); break; }
    }
}
__device__ __forceinline__ void mbar_arrive(uint32_t a) {
    asm volatile("mbarrier.arrive.shared::cta.b64 _, [%0];" ::"r"(a) : "memory");
}
__device__ __forceinline__ void mbar_arrive_cta(uint32_t a, uint32_t cta) {
    asm volatile("{\n.reg .b32 r;\nmapa.shared::cluster.u32 r, %0, %1;\nmbarrier.arrive.shared::cluster.b64 _, [r];\n}"
                 ::"r"(a), "r"(cta) : "memory");
}
#define ELECT_ "{\n.reg .pred e;\nelect.sync _|e, 0xffffffff;\n@e "
__device__ __forceinline__ void mbar_arrive_one(uint32_t a) {
    asm volatile(ELECT_ "mbarrier.arrive.shared::cta.b64 _, [%0];\n}" ::"r"(a) : "memory");
}
__device__ __forceinline__ void mbar_expect(uint32_t a, uint32_t bytes) {
    asm volatile(ELECT_ "mbarrier.arrive.expect_tx.shared::cta.b64 _, [%0], %1;\n}" ::"r"(a), "r"(bytes) : "memory");
}
__device__ __forceinline__ void tma_2d(uint32_t dst, const CUtensorMap* tm, int c0, int c1, uint32_t bar) {
    asm volatile(ELECT_ "cp.async.bulk.tensor.2d.shared::cluster.global.mbarrier::complete_tx::bytes [%0], [%1, {%3, %4}], [%2];\n}"
                 ::"r"(dst), "l"(tm), "r"(bar), "r"(c0), "r"(c1) : "memory");
}
__device__ __forceinline__ void tma_2d_mc(uint32_t dst, const CUtensorMap* tm, int c0, int c1, uint32_t bar) {
    asm volatile(ELECT_ "cp.async.bulk.tensor.2d.shared::cluster.global.mbarrier::complete_tx::bytes.multicast::cluster [%0], [%1, {%3, %4}], [%2], %5;\n}"
                 ::"r"(dst), "l"(tm), "r"(bar), "r"(c0), "r"(c1), "h"((uint16_t)3) : "memory");
}
__device__ __forceinline__ void bulk_load(uint32_t dst, const void* src, uint32_t bytes, uint32_t bar) {
    asm volatile(ELECT_ "cp.async.bulk.shared::cluster.global.mbarrier::complete_tx::bytes [%0], [%1], %2, [%3];\n}"
                 ::"r"(dst), "l"(src), "r"(bytes), "r"(bar) : "memory");
}
__device__ __forceinline__ void bulk_load_mc(uint32_t dst, const void* src, uint32_t bytes, uint32_t bar) {
    asm volatile(ELECT_ "cp.async.bulk.shared::cluster.global.mbarrier::complete_tx::bytes.multicast::cluster [%0], [%1], %2, [%3], %4;\n}"
                 ::"r"(dst), "l"(src), "r"(bytes), "r"(bar), "h"((uint16_t)3) : "memory");
}
__device__ __forceinline__ void bulk_store(void* dst, uint32_t src, uint32_t bytes) {
    asm volatile(ELECT_ "cp.async.bulk.global.shared::cta.bulk_group [%0], [%1], %2;\n}" ::"l"(dst), "r"(src), "r"(bytes) : "memory");
}
__device__ __forceinline__ void bulk_reduce_f32(void* dst, uint32_t src, uint32_t bytes) {
    asm volatile(ELECT_ "cp.reduce.async.bulk.global.shared::cta.bulk_group.add.f32 [%0], [%1], %2;\n}" ::"l"(dst), "r"(src), "r"(bytes) : "memory");
}
__device__ __forceinline__ void tma_store_2d(const CUtensorMap* tm, int c0, int c1, uint32_t src) {
    asm volatile(ELECT_ "cp.async.bulk.tensor.2d.global.shared::cta.bulk_group [%0, {%2, %3}], [%1];\n}"
                 ::"l"(tm), "r"(src), "r"(c0), "r"(c1) : "memory");
}
__device__ __forceinline__ void tma_add_2d(const CUtensorMap* tm, int c0, int c1, uint32_t src) {
    asm volatile(ELECT_ "cp.reduce.async.bulk.tensor.2d.global.shared::cta.add.tile.bulk_group [%0, {%2, %3}], [%1];\n}"
                 ::"l"(tm), "r"(src), "r"(c0), "r"(c1) : "memory");
}
__device__ __forceinline__ void flag_signal(uint32_t* p) {
    asm volatile(ELECT_ "red.release.gpu.global.add.u32 [%0], 1;\n}" ::"l"(p) : "memory");
}
__device__ __forceinline__ void bulk_commit() { asm volatile("cp.async.bulk.commit_group;" ::: "memory"); }
__device__ __forceinline__ void bulk_wait_read() { asm volatile("cp.async.bulk.wait_group.read 0;" ::: "memory"); }
__device__ __forceinline__ void bulk_wait_all() { asm volatile("cp.async.bulk.wait_group 0;" ::: "memory"); }
__device__ __forceinline__ void fence_async_smem() { asm volatile("fence.proxy.async.shared::cta;" ::: "memory"); }
__device__ __forceinline__ void fence_async_global() { asm volatile("fence.proxy.async.global;" ::: "memory"); }
__device__ __forceinline__ uint32_t ld_acquire(const uint32_t* p) {
    uint32_t v;
    asm volatile("ld.acquire.gpu.global.u32 %0, [%1];" : "=r"(v) : "l"(p) : "memory");
    return v;
}
__device__ __forceinline__ uint32_t lds32(uint32_t addr) {
    uint32_t v;
    asm volatile("ld.shared.u32 %0, [%1];" : "=r"(v) : "r"(addr) : "memory");
    return v;
}
__device__ __forceinline__ void ticket_publish(uint32_t addr, uint32_t v) {
    asm volatile("st.release.cta.shared.u32 [%0], %1;" ::"r"(addr), "r"(v) : "memory");
}
__device__ __forceinline__ uint32_t ticket_wait(uint32_t addr, uint32_t v) {
    uint32_t t, n = 0;
    while (true) {
        asm volatile("ld.acquire.cta.shared.u32 %0, [%1];" : "=r"(t) : "r"(addr) : "memory");
        if (t >= v) break;
        if (++n > SPIN_LIMIT) { abort_launch(); break; }
        __nanosleep(40);
    }
    return t;
}
__device__ __forceinline__ void bar_sync(int id, int n) { asm volatile("bar.sync %0, %1;" ::"r"(id), "r"(n) : "memory"); }
__device__ __forceinline__ void bar_arrive(int id, int n) { asm volatile("bar.arrive %0, %1;" ::"r"(id), "r"(n) : "memory"); }
__device__ __forceinline__ void cluster_arrive() { asm volatile("barrier.cluster.arrive.relaxed;" ::: "memory"); }
__device__ __forceinline__ void cluster_wait() { asm volatile("barrier.cluster.wait;" ::: "memory"); }
__device__ __forceinline__ uint32_t pack_bf16(float lo, float hi) {
    uint32_t r;
    asm("cvt.rn.bf16x2.f32 %0, %1, %2;" : "=r"(r) : "f"(hi), "f"(lo));
    return r;
}
__device__ __forceinline__ float ex2(float x) {
    float y;
    asm("ex2.approx.ftz.f32 %0, %1;" : "=f"(y) : "f"(x));
    return y;
}
__device__ __forceinline__ uint32_t movmatrix(uint32_t a) {
    uint32_t d;
    asm("movmatrix.sync.aligned.m8n8.trans.b16 %0, %1;" : "=r"(d) : "r"(a));
    return d;
}
__device__ __forceinline__ void stmatrix_x4(uint32_t addr, uint32_t a, uint32_t b, uint32_t c, uint32_t d) {
    asm volatile("stmatrix.sync.aligned.m8n8.x4.shared.b16 [%0], {%1, %2, %3, %4};" ::"r"(addr), "r"(a), "r"(b), "r"(c), "r"(d) : "memory");
}
__device__ __forceinline__ void mma16816(float (&c)[4], uint32_t a0, uint32_t a1, uint32_t a2, uint32_t a3, uint32_t b0, uint32_t b1) {
    asm("mma.sync.aligned.m16n8k16.row.col.f32.bf16.bf16.f32 {%0,%1,%2,%3}, {%4,%5,%6,%7}, {%8,%9}, {%0,%1,%2,%3};"
                 : "+f"(c[0]), "+f"(c[1]), "+f"(c[2]), "+f"(c[3]) : "r"(a0), "r"(a1), "r"(a2), "r"(a3), "r"(b0), "r"(b1));
}

__device__ __forceinline__ uint32_t desc_lo(uint32_t addr, uint32_t lbo) { return ((addr & 0x3FFFF) >> 4) | ((lbo >> 4) << 16); }
#define DESC_HI "0x40000040"
__device__ __forceinline__ void wg_fence() { asm volatile("wgmma.fence.sync.aligned;" ::: "memory"); }
__device__ __forceinline__ void wg_commit() { asm volatile("wgmma.commit_group.sync.aligned;" ::: "memory"); }
template <int N> __device__ __forceinline__ void wg_wait() { asm volatile("wgmma.wait_group.sync.aligned %0;" ::"n"(N) : "memory"); }

#define R8(a, i) "+f"(a[i]), "+f"(a[i + 1]), "+f"(a[i + 2]), "+f"(a[i + 3]), "+f"(a[i + 4]), "+f"(a[i + 5]), "+f"(a[i + 6]), "+f"(a[i + 7])
#define R32(a, i) R8(a, i), R8(a, i + 8), R8(a, i + 16), R8(a, i + 24)
#define R64(a, i) R32(a, i), R32(a, i + 32)
#define L32A "%0,%1,%2,%3,%4,%5,%6,%7,%8,%9,%10,%11,%12,%13,%14,%15,%16,%17,%18,%19,%20,%21,%22,%23,%24,%25,%26,%27,%28,%29,%30,%31"
#define L32B "%32,%33,%34,%35,%36,%37,%38,%39,%40,%41,%42,%43,%44,%45,%46,%47,%48,%49,%50,%51,%52,%53,%54,%55,%56,%57,%58,%59,%60,%61,%62,%63"
#define L32C "%64,%65,%66,%67,%68,%69,%70,%71,%72,%73,%74,%75,%76,%77,%78,%79,%80,%81,%82,%83,%84,%85,%86,%87,%88,%89,%90,%91,%92,%93,%94,%95"
#define L32D "%96,%97,%98,%99,%100,%101,%102,%103,%104,%105,%106,%107,%108,%109,%110,%111,%112,%113,%114,%115,%116,%117,%118,%119,%120,%121,%122,%123,%124,%125,%126,%127"

#define W8(a, i) "=f"(a[i]), "=f"(a[i + 1]), "=f"(a[i + 2]), "=f"(a[i + 3]), "=f"(a[i + 4]), "=f"(a[i + 5]), "=f"(a[i + 6]), "=f"(a[i + 7])
#define W32(a, i) W8(a, i), W8(a, i + 8), W8(a, i + 16), W8(a, i + 24)
#define W64(a, i) W32(a, i), W32(a, i + 32)

#define SS128_ "{\n.reg .b64 a, b;\nmov.b64 a, {%64, " DESC_HI "};\nmov.b64 b, {%65, " DESC_HI "};\n" \
               "wgmma.mma_async.sync.aligned.m64n128k16.f32.bf16.bf16 {" L32A "," L32B "}, a, b, %66, 1, 1, 0, %67;\n}"
template <int TB, int ACC> __device__ __forceinline__ void wgmma_ss128(float (&d)[64], uint32_t da, uint32_t db) {
    if constexpr (ACC) asm volatile(SS128_ : R64(d, 0) : "r"(da), "r"(db), "n"(1), "n"(TB));
    else asm volatile(SS128_ : W64(d, 0) : "r"(da), "r"(db), "n"(0), "n"(TB));
}
#define RS128_ "{\n.reg .b64 b;\nmov.b64 b, {%68, " DESC_HI "};\n" \
               "wgmma.mma_async.sync.aligned.m64n128k16.f32.bf16.bf16 {" L32A "," L32B "}, {%64,%65,%66,%67}, b, %69, 1, 1, %70;\n}"
template <int TB, int ACC> __device__ __forceinline__ void wgmma_rs128(float (&d)[64], uint32_t a0, uint32_t a1, uint32_t a2, uint32_t a3, uint32_t db) {
    if constexpr (ACC) asm volatile(RS128_ : R64(d, 0) : "r"(a0), "r"(a1), "r"(a2), "r"(a3), "r"(db), "n"(1), "n"(TB));
    else asm volatile(RS128_ : W64(d, 0) : "r"(a0), "r"(a1), "r"(a2), "r"(a3), "r"(db), "n"(0), "n"(TB));
}
#define RS64_ "{\n.reg .b64 b;\nmov.b64 b, {%36, " DESC_HI "};\n" \
              "wgmma.mma_async.sync.aligned.m64n64k16.f32.bf16.bf16 {" L32A "}, {%32,%33,%34,%35}, b, %37, 1, 1, 0;\n}"
template <int ACC> __device__ __forceinline__ void wgmma_rs64(float (&d)[64], uint32_t a0, uint32_t a1, uint32_t a2, uint32_t a3, uint32_t db) {
    if constexpr (ACC) asm volatile(RS64_ : R32(d, 0) : "r"(a0), "r"(a1), "r"(a2), "r"(a3), "r"(db), "n"(1));
    else asm volatile(RS64_ : W32(d, 0) : "r"(a0), "r"(a1), "r"(a2), "r"(a3), "r"(db), "n"(0));
}
#define SS256_ "{\n.reg .b64 a, b;\nmov.b64 a, {%128, " DESC_HI "};\nmov.b64 b, {%129, " DESC_HI "};\n" \
               "wgmma.mma_async.sync.aligned.m64n256k16.f32.bf16.bf16 {" L32A "," L32B "," L32C "," L32D "}, a, b, %130, 1, 1, 0, %131;\n}"
template <int TB, int ACC> __device__ __forceinline__ void wgmma_ss256(float (&d)[128], uint32_t da, uint32_t db) {
    if constexpr (ACC) asm volatile(SS256_ : R64(d, 0), R64(d, 64) : "r"(da), "r"(db), "n"(1), "n"(TB));
    else asm volatile(SS256_ : W64(d, 0), W64(d, 64) : "r"(da), "r"(db), "n"(0), "n"(TB));
}
template <int N> __device__ __forceinline__ void zero_acc(float (&d)[N]) {
#pragma unroll
    for (int i = 0; i < N; i++) d[i] = 0.f;
}
__device__ __forceinline__ void pin32(float (&d)[64]) { asm volatile("" : R32(d, 0)::"memory"); }
__device__ __forceinline__ void pin64(float (&d)[64]) { asm volatile("" : R64(d, 0)::"memory"); }
__device__ __forceinline__ void pin128(float (&d)[128]) { asm volatile("" : R64(d, 0), R64(d, 64)::"memory"); }

struct Ring {
    uint32_t slot, phase;
    __device__ __forceinline__ void advance() {
        if (++slot == NSLOT) { slot = 0; phase ^= 1; }
    }
};

#define FENCE_IN_STORE_WARP 1
struct Consumer {
    uint32_t sbase;
    uint32_t stg;
    uint32_t stm_off;
    uint32_t nstores;
    uint32_t pending;
    int role;
    int wg, tid;
    Ring ring;

    __device__ __forceinline__ uint32_t bars() const { return sbase + BAR_OFF; }
    __device__ __forceinline__ void make_uniform() {
        const uint32_t st = __shfl_sync(0xffffffffu, ring.slot | ring.phase << 7 | (nstores & 1) << 4 | role << 6 | pending << 8, 0);
        ring.slot = st & 15;
        ring.phase = (st >> 7) & 1;
        nstores = (st >> 4) & 1;
        pending = st >> 8;
        role = (st >> 6) & 1;
    }
    __device__ __forceinline__ uint32_t acquire() {
        mbar_wait(bars() + BAR_FULL + ring.slot * 8, ring.phase);
        uint32_t s = ring.slot;
        ring.advance();
        return s;
    }
    __device__ __forceinline__ uint32_t skip() {
        uint32_t s = ring.slot;
        ring.advance();
        return s;
    }
    __device__ __forceinline__ void release(uint32_t s) const {
        if (tid < 2) mbar_arrive_cta(bars() + BAR_EMPTY + s * 8, tid);
    }
    __device__ __forceinline__ uint32_t slot_addr(uint32_t s) const { return sbase + s * SLOT_BYTES; }
    __device__ __forceinline__ uint32_t slot_desc(uint32_t s, uint32_t lbo) const { return desc_lo(sbase, lbo) + s * (SLOT_BYTES >> 4); }
    __device__ __forceinline__ void stg_write(uint32_t buf, const uint32_t* pk) const {
#pragma unroll
        for (int i = 0; i < 8; i++)
            stmatrix_x4(buf + (stm_off ^ ((i & 3) * 32)) + (i >> 2) * 8192, pk[4 * i], pk[4 * i + 1], pk[4 * i + 2], pk[4 * i + 3]);
    }
    __device__ __forceinline__ void write_first(const uint32_t* pk) const {
        mbar_wait(bars() + BAR_STG_EMPTY + wg * 8, (nstores & 1) ^ 1);
        stg_write(stg, pk);
    }
    __device__ __forceinline__ void submit_first() {
        if (!FENCE_IN_STORE_WARP) fence_async_smem();
        mbar_arrive(bars() + BAR_STG_FULL + wg * 8);
        nstores++;
    }
    __device__ __forceinline__ void flush(const uint32_t (&pend)[32]) {
        if (pending) {
            write_first(pend);
            submit_first();
            pending = 0;
        }
    }
    __device__ __forceinline__ uint32_t write_second(const uint32_t* pk) {
        uint32_t s = acquire();
        stg_write(slot_addr(s) + wg * 16384, pk);
        return s;
    }
    __device__ __forceinline__ void submit_second() const {
        if (!FENCE_IN_STORE_WARP) fence_async_smem();
        mbar_arrive(bars() + BAR_STG2_FULL + wg * 8);
    }
};

template <int ACC0>
__device__ __forceinline__ void gemm_chunk(float (&acc)[128], uint32_t a, uint32_t b) {
    wg_fence();
    wgmma_ss256<1, ACC0>(acc, a, b);
#pragma unroll
    for (int kk = 1; kk < 4; kk++) wgmma_ss256<1, 1>(acc, a + kk * 2, b + kk * 128);
    wg_commit();
}
#define GEMM_FLUSH 1
#define GEMM_SKEW 1
__device__ __forceinline__ void gemm_mainloop(Consumer& c, float (&acc)[128], int npairs, const uint32_t (&pend)[32]) {
    TR(c, 8);
    uint32_t s0 = c.acquire();
    uint32_t s1 = c.skip();
    TR(c, 9);
    gemm_chunk<0>(acc, c.slot_desc(s1, 16) + c.wg * 512, c.slot_desc(s0, 8192));
#pragma unroll 1
    for (int p = 1;; p++) {
        uint32_t s2 = c.acquire();
        gemm_chunk<1>(acc, c.slot_desc(s1, 16) + c.wg * 512 + 1024, c.slot_desc(s2, 8192));
        if (GEMM_SKEW && p == npairs && c.role == 1) bar_arrive(4, 256);
        wg_wait<1>();
        c.release(s0);
        if (npairs == 4) TR(c, 10);
        s0 = s2;
        if (p == npairs) break;
        const bool hold = GEMM_SKEW && p == npairs - 1 && c.role == 0;
        if (hold) {
            wg_wait<0>();
            c.release(s1);
            c.release(s2);
            bar_sync(4, 256);
        }
        uint32_t n0 = c.acquire();
        uint32_t n1 = c.skip();
        gemm_chunk<1>(acc, c.slot_desc(n1, 16) + c.wg * 512, c.slot_desc(n0, 8192));
        wg_wait<1>();
        if (!hold) {
            c.release(s1);
            c.release(s2);
        }
        if (p >= GEMM_FLUSH) c.flush(pend);
        s0 = n0;
        s1 = n1;
    }
    wg_wait<0>();
    pin128(acc);
    TR(c, 11);
    c.release(s1);
    c.release(s0);
}

__device__ __forceinline__ float quad_max(float x) {
    x = fmaxf(x, __shfl_xor_sync(0xffffffffu, x, 1));
    return fmaxf(x, __shfl_xor_sync(0xffffffffu, x, 2));
}
__device__ __forceinline__ float quad_sum(float x) {
    x += __shfl_xor_sync(0xffffffffu, x, 1);
    return x + __shfl_xor_sync(0xffffffffu, x, 2);
}
__device__ __forceinline__ float rcp(float x) {
    float y;
    asm("rcp.approx.ftz.f32 %0, %1;" : "=f"(y) : "f"(x));
    return y;
}
__device__ __forceinline__ void ldmatrix_x4(uint32_t* d, uint32_t addr) {
    asm volatile("ldmatrix.sync.aligned.m8n8.x4.shared.b16 {%0, %1, %2, %3}, [%4];"
                 : "=r"(d[0]), "=r"(d[1]), "=r"(d[2]), "=r"(d[3]) : "r"(addr) : "memory");
}
__device__ __forceinline__ void ldmatrix_x4_trans(uint32_t* d, uint32_t addr) {
    asm volatile("ldmatrix.sync.aligned.m8n8.x4.trans.shared.b16 {%0, %1, %2, %3}, [%4];"
                 : "=r"(d[0]), "=r"(d[1]), "=r"(d[2]), "=r"(d[3]) : "r"(addr) : "memory");
}
#define A_ILP 2
constexpr float FM_LIMIT = 1099511627776.f;
constexpr uint32_t BF16_ONES = 0x3F803F80u;
template <bool EXACT>
__device__ __forceinline__ void features(const uint32_t* x, const uint32_t (&w)[4], float (&e)[2][8]) {
    constexpr float LOG2E = 1.4426950408889634f;
    float p0[4] = {0.f, 0.f, 0.f, 0.f}, p1[4] = {0.f, 0.f, 0.f, 0.f};
    mma16816(p0, x[0], x[1], x[2], x[3], w[0], w[1]);
    mma16816(p1, x[0], x[1], x[2], x[3], w[2], w[3]);
#pragma unroll
    for (int r = 0; r < 2; r++) {
        const float t[4] = {p0[2 * r] * LOG2E, p0[2 * r + 1] * LOG2E, p1[2 * r] * LOG2E, p1[2 * r + 1] * LOG2E};
        if (EXACT) {
            const float mx = quad_max(fmaxf(fmaxf(t[0], t[1]), fmaxf(t[2], t[3])));
            const float mn = -quad_max(-fminf(fminf(t[0], t[1]), fminf(t[2], t[3])));
#pragma unroll
            for (int i = 0; i < 4; i++) {
                e[r][i] = ex2(t[i] - mx);
                e[r][4 + i] = ex2(mn - t[i]);
            }
        } else {
#pragma unroll
            for (int i = 0; i < 4; i += 2) {
                const float a = ex2(t[i]), b = ex2(t[i + 1]), inv = rcp(a * b);
                e[r][i] = a;
                e[r][i + 1] = b;
                e[r][4 + i] = inv * b;
                e[r][5 + i] = inv * a;
            }
        }
    }
}
__device__ __forceinline__ void pack_features(uint32_t (&a)[4], const float (&e)[2][8], int s, float k0, float k1) {
    a[0] = pack_bf16(e[0][4 * s] * k0, e[0][4 * s + 1] * k0);
    a[1] = pack_bf16(e[1][4 * s] * k1, e[1][4 * s + 1] * k1);
    a[2] = pack_bf16(e[0][4 * s + 2] * k0, e[0][4 * s + 3] * k0);
    a[3] = pack_bf16(e[1][4 * s + 2] * k1, e[1][4 * s + 3] * k1);
}

__device__ __forceinline__ uint32_t ld_pack2(uint32_t addr) {
    float x, y;
    asm volatile("ld.shared.v2.f32 {%0, %1}, [%2];" : "=f"(x), "=f"(y) : "r"(addr));
    return pack_bf16(x, y);
}

__device__ __forceinline__ uint32_t head_frag_off(int w8, int lane) {
    return (w8 >> 2) * 8192 + (lane & 15) * 128 + (((2 * (w8 & 3) + (lane >> 4)) ^ (lane & 7)) * 16);
}
__device__ __forceinline__ uint32_t row_group_off(int g) { return (g >> 2) * 16384 + (g & 3) * 2048; }

template <bool EXACT>
__device__ __forceinline__ bool a1_group(const uint32_t* x, const uint32_t (&w)[4], uint32_t (&phi)[2][4]) {
    float e[2][8], sum[2][4];
    features<EXACT>(x, w, e);
#pragma unroll
    for (int s = 0; s < 2; s++) {
        uint32_t a[4];
        pack_features(a, e, s, 1.f, 1.f);
        sum[s][0] = sum[s][1] = sum[s][2] = sum[s][3] = 0.f;
        mma16816(sum[s], a[0], a[1], a[2], a[3], BF16_ONES, BF16_ONES);
    }
    const float i0 = rcp(sum[0][0] * sum[1][0]), i1 = rcp(sum[0][2] * sum[1][2]);
    pack_features(phi[0], e, 0, i0 * sum[1][0], i1 * sum[1][2]);
    pack_features(phi[1], e, 1, i0 * sum[0][0], i1 * sum[0][2]);
    return sum[0][0] <= FM_LIMIT && sum[1][0] <= FM_LIMIT && sum[0][2] <= FM_LIMIT && sum[1][2] <= FM_LIMIT;
}

__device__ __forceinline__ void a1_epilogue(uint32_t kbuf, uint32_t vbuf, uint32_t tab, int w8, int lane) {
    constexpr int U = A_ILP;
    uint32_t w[4];
    ldmatrix_x4_trans(w, tab + TAB_W_OFF + w8 * 512 + (lane & 15) * 32 + (lane >> 4) * 16);
    const uint32_t off = head_frag_off(w8, lane);
    float kv[4][4], z[4][4];
#pragma unroll
    for (int t = 0; t < 4; t++)
#pragma unroll
        for (int i = 0; i < 4; i++) kv[t][i] = z[t][i] = 0.f;
#pragma unroll 1
    for (int g = 0; g < 8; g += U) {
        uint32_t x[U][4], v[U][4], phi[U][2][4];
        bool safe = true;
#pragma unroll
        for (int u = 0; u < U; u++) {
            ldmatrix_x4(x[u], kbuf + off + row_group_off(g + u));
            ldmatrix_x4_trans(v[u], vbuf + off + row_group_off(g + u));
        }
#pragma unroll
        for (int u = 0; u < U; u++) safe &= a1_group<false>(x[u], w, phi[u]);
        if (__any_sync(0xffffffffu, !safe)) {
#pragma unroll
            for (int u = 0; u < U; u++) a1_group<true>(x[u], w, phi[u]);
        }
#pragma unroll
        for (int u = 0; u < U; u++)
#pragma unroll
            for (int t = 0; t < 4; t++) {
                uint32_t b0 = movmatrix(phi[u][t >> 1][2 * (t & 1)]), b1 = movmatrix(phi[u][t >> 1][2 * (t & 1) + 1]);
                mma16816(kv[t], v[u][0], v[u][2], v[u][1], v[u][3], b0, b1);
                mma16816(z[t], BF16_ONES, BF16_ONES, BF16_ONES, BF16_ONES, b0, b1);
            }
    }
    const uint32_t dst = tab + (w8 * AKV_HEAD + (lane >> 2) * AKV_ROW + (lane & 3) * 2) * 4;
#pragma unroll
    for (int t = 0; t < 5; t++) {
        const float a = t < 4 ? kv[t & 3][0] : 0.f, b = t < 4 ? kv[t & 3][1] : 0.f, c = t < 4 ? kv[t & 3][2] : 0.f, d = t < 4 ? kv[t & 3][3] : 0.f;
        const float e = t < 4 ? z[t & 3][0] : 0.f, f = t < 4 ? z[t & 3][1] : 0.f;
        asm volatile("st.shared.v2.f32 [%0], {%1, %2};" ::"r"(dst + 32 * t), "f"(a), "f"(b) : "memory");
        asm volatile("st.shared.v2.f32 [%0], {%1, %2};" ::"r"(dst + 32 * t + 32 * AKV_ROW), "f"(c), "f"(d) : "memory");
        if (lane < 4) asm volatile("st.shared.v2.f32 [%0], {%1, %2};" ::"r"(dst + 32 * t + 64 * AKV_ROW), "f"(e), "f"(f) : "memory");
    }
}

template <bool EXACT>
__device__ __forceinline__ bool a2_group(const uint32_t* x, const uint32_t (&w)[4], const uint32_t (&kb)[2][3][2], uint32_t (&o)[4]) {
    float e[2][8], n[2][3][4];
    features<EXACT>(x, w, e);
#pragma unroll
    for (int s = 0; s < 2; s++) {
        uint32_t a[4];
        pack_features(a, e, s, 1.f, 1.f);
#pragma unroll
        for (int t = 0; t < 3; t++) {
            n[s][t][0] = n[s][t][1] = n[s][t][2] = n[s][t][3] = 0.f;
            mma16816(n[s][t], a[0], a[1], a[2], a[3], kb[s][t][0], kb[s][t][1]);
        }
    }
    bool safe = true;
#pragma unroll
    for (int r = 0; r < 2; r++) {
        const float sp = n[0][2][2 * r + 1], sn = n[1][2][2 * r + 1];
        const float inv = rcp(fmaf(fmaf(1e-6f, sp, n[0][2][2 * r]), sn, n[1][2][2 * r] * sp));
        const float kp = sn * inv, kn = sp * inv;
        o[r] = pack_bf16(fmaf(n[0][0][2 * r], kp, n[1][0][2 * r] * kn), fmaf(n[0][0][2 * r + 1], kp, n[1][0][2 * r + 1] * kn));
        o[2 + r] = pack_bf16(fmaf(n[0][1][2 * r], kp, n[1][1][2 * r] * kn), fmaf(n[0][1][2 * r + 1], kp, n[1][1][2 * r + 1] * kn));
        safe = safe && sp <= FM_LIMIT && sn <= FM_LIMIT;
    }
    return safe;
}

__device__ __forceinline__ void a2_epilogue(uint32_t buf, uint32_t tab, int w8, int lane) {
    constexpr int U = A_ILP;
    uint32_t w[4], kb[2][3][2];
    ldmatrix_x4_trans(w, tab + TAB_W_OFF + w8 * 512 + (lane & 15) * 32 + (lane >> 4) * 16);
    {
        const uint32_t kv = tab + (w8 * AKV_HEAD + (lane >> 2) * AKV_ROW + (lane & 3) * 2) * 4;
        const uint32_t zp = tab + (w8 * AKV_HEAD + 16 * AKV_ROW + (lane & 3) * 2) * 4;
#pragma unroll
        for (int s = 0; s < 2; s++)
#pragma unroll
            for (int i = 0; i < 2; i++) {
                kb[s][0][i] = ld_pack2(kv + 64 * s + 32 * i);
                kb[s][1][i] = ld_pack2(kv + 32 * AKV_ROW + 64 * s + 32 * i);
                const uint32_t zf = ld_pack2(zp + 64 * s + 32 * i);
                kb[s][2][i] = (lane & 4) ? BF16_ONES : zf;
            }
    }
    const uint32_t off = buf + head_frag_off(w8, lane);
#pragma unroll 1
    for (int g = 0; g < 8; g += U) {
        uint32_t x[U][4], o[U][4];
        bool safe = true;
#pragma unroll
        for (int u = 0; u < U; u++) ldmatrix_x4(x[u], off + row_group_off(g + u));
#pragma unroll
        for (int u = 0; u < U; u++) safe &= a2_group<false>(x[u], w, kb, o[u]);
        if (__any_sync(0xffffffffu, !safe)) {
#pragma unroll
            for (int u = 0; u < U; u++) a2_group<true>(x[u], w, kb, o[u]);
        }
#pragma unroll
        for (int u = 0; u < U; u++) stmatrix_x4(off + row_group_off(g + u), o[u][0], o[u][1], o[u][2], o[u][3]);
    }
}

constexpr float SM_SCALE_LOG2 = 0.08838834764831845f * 1.4426950408889634f;
constexpr float SM_BIAS = 96.f;
constexpr float SM_LIMIT = 1073741824.f;
constexpr uint32_t V_SCALE_BF16X2 = 0x53805380u;
constexpr float V_UNSCALE = 9.094947017729282e-13f;

template <int NG>
__device__ __forceinline__ float row_max(const float (&s)[64], int r) {
    float t[2] = {fmaxf(s[2 * r], s[2 * r + 1]), -INFINITY};
#pragma unroll
    for (int i = 1; i < NG; i++) t[i & 1] = fmaxf(t[i & 1], fmaxf(s[4 * i + 2 * r], s[4 * i + 2 * r + 1]));
    return quad_max(NG > 1 ? fmaxf(t[0], t[1]) : t[0]);
}
__device__ __forceinline__ float neg_offset(float mx) { return fmaf(mx, -SM_SCALE_LOG2, -SM_BIAS); }
__device__ __forceinline__ bool sums_unsafe(float r0, float r1) {
    return __any_sync(0xffffffffu, !(r0 <= SM_LIMIT && r1 <= SM_LIMIT));
}
template <int I0, int I1>
__device__ __forceinline__ void exp_pack(const float (&s)[64], uint32_t (&p)[32], float nmu0, float nmu1, float (&a)[4]) {
#pragma unroll
    for (int i = I0; i < I1; i++) {
        float e0 = ex2(fmaf(s[4 * i], SM_SCALE_LOG2, nmu0)), e1 = ex2(fmaf(s[4 * i + 1], SM_SCALE_LOG2, nmu0));
        float e2 = ex2(fmaf(s[4 * i + 2], SM_SCALE_LOG2, nmu1)), e3 = ex2(fmaf(s[4 * i + 3], SM_SCALE_LOG2, nmu1));
        a[0] += e0;
        a[1] += e1;
        a[2] += e2;
        a[3] += e3;
        p[2 * i] = pack_bf16(e0, e1);
        p[2 * i + 1] = pack_bf16(e2, e3);
    }
}
template <int I0, int I1> __device__ __forceinline__ void pin_p(uint32_t (&p)[32]) {
#pragma unroll
    for (int i = I0; i < I1; i += 4) asm volatile("" : "+r"(p[i]), "+r"(p[i + 1]), "+r"(p[i + 2]), "+r"(p[i + 3])::"memory");
}
__device__ __forceinline__ void issue_qk(float (&s)[64], const uint32_t (&q)[32], uint32_t k) {
    wgmma_rs128<0, 0>(s, q[0], q[1], q[2], q[3], k);
#pragma unroll
    for (int kk = 1; kk < 8; kk++)
        wgmma_rs128<0, 1>(s, q[4 * kk], q[4 * kk + 1], q[4 * kk + 2], q[4 * kk + 3], k + (kk >> 2) * 1024 + (kk & 3) * 2);
    wg_commit();
}
template <int K0, int K1>
__device__ __forceinline__ void issue_pv(float (&o)[64], const uint32_t (&p)[32], uint32_t v) {
#pragma unroll
    for (int kk = K0; kk < K1; kk++) wgmma_rs128<1, 1>(o, p[4 * kk], p[4 * kk + 1], p[4 * kk + 2], p[4 * kk + 3], v + kk * 128);
    wg_commit();
}
template <int ACC0>
__device__ __forceinline__ void qproj_chunk(float (&s)[64], uint32_t a, uint32_t b) {
    wg_fence();
    wgmma_ss128<1, ACC0>(s, a, b);
#pragma unroll
    for (int kk = 1; kk < 4; kk++) wgmma_ss128<1, 1>(s, a + kk * 2, b + kk * 128);
    wg_commit();
}

#define QPROJ_FLUSH 3
#define PV_SPLIT 3

#define SM_SEED 2
#define SKIP_HALF_PV 0
#define ROLE_FLIP 1

template <int NG>
__device__ __forceinline__ void first_block(float (&s)[64], uint32_t (&p)[32], int lim, float& nmu0, float& nmu1, float& l0, float& l1) {
#pragma unroll
    for (int i = 0; i < 8; i++) {
        float* e = &s[4 * (NG - 8 + i)];
        if (8 * i > lim) e[0] = -INFINITY;
        if (8 * i + 1 > lim) e[1] = -INFINITY;
        if (8 * i > lim + 8) e[2] = -INFINITY;
        if (8 * i + 1 > lim + 8) e[3] = -INFINITY;
    }
    nmu0 = neg_offset(row_max<SM_SEED>(s, 0));
    nmu1 = neg_offset(row_max<SM_SEED>(s, 1));
    float a[4] = {0.f, 0.f, 0.f, 0.f};
    exp_pack<0, NG>(s, p, nmu0, nmu1, a);
    l0 = a[0] + a[1];
    l1 = a[2] + a[3];
    if (sums_unsafe(l0, l1)) {
        nmu0 = neg_offset(row_max<NG>(s, 0));
        nmu1 = neg_offset(row_max<NG>(s, 1));
        float b[4] = {0.f, 0.f, 0.f, 0.f};
        exp_pack<0, NG>(s, p, nmu0, nmu1, b);
        l0 = b[0] + b[1];
        l1 = b[2] + b[3];
    }
}

__device__ __forceinline__ void attention_item(Consumer& c, int j, int rank, uint32_t (&p)[32]) {
    float s[64], o[64];
    uint32_t q[32];
    const int lane = c.tid & 31, warp = c.tid >> 5;
    TR(c, 0);
    {

        uint32_t prev = c.acquire();
        TR(c, 1);
        qproj_chunk<0>(s, c.slot_desc(prev, 16) + c.wg * 512, c.slot_desc(prev, 8192) + 1024);
#pragma unroll 1
        for (int ch = 1; ch < 8; ch++) {
            uint32_t sl = c.acquire();
            qproj_chunk<1>(s, c.slot_desc(sl, 16) + c.wg * 512, c.slot_desc(sl, 8192) + 1024);
            wg_wait<1>();
            c.release(prev);
            prev = sl;
            if (ch >= QPROJ_FLUSH) c.flush(p);
        }
        zero_acc(o);
        wg_wait<0>();
        pin64(s);
        TR(c, 2);
        c.release(prev);
#pragma unroll
        for (int i = 0; i < 32; i++) q[i] = pack_bf16(s[2 * i], s[2 * i + 1]);
    }
    const bool lead = c.role == 1;
    const bool half = c.role == rank;
    const int nblk = 2 * j + 1 + c.role;
    float nmu0, nmu1, l0, l1;
    {
        if (!lead) c.release(c.acquire());
        uint32_t sk = c.acquire();
        TR(c, 3);
        if (!lead) bar_sync(1 + c.wg, 256);
        const int lim = warp * 16 + (lane >> 2) - (lane & 3) * 2;
        const uint32_t kd = c.slot_desc(sk, 16);
        if (half) {
            wg_fence();
            wgmma_rs64<0>(s, q[0], q[1], q[2], q[3], kd);
#pragma unroll
            for (int kk = 1; kk < 8; kk++)
                wgmma_rs64<1>(s, q[4 * kk], q[4 * kk + 1], q[4 * kk + 2], q[4 * kk + 3], kd + (kk >> 2) * 1024 + (kk & 3) * 2);
            wg_commit();
            bar_arrive(2 - c.wg, 256);
            wg_wait<0>();
            pin32(s);
            TR(c, 4);
            c.release(sk);
            first_block<8>(s, p, lim, nmu0, nmu1, l0, l1);
#pragma unroll
            for (int i = 16; i < 32; i++) p[i] = 0;
        } else {
            wg_fence();
            issue_qk(s, q, kd);
            bar_arrive(2 - c.wg, 256);
            wg_wait<0>();
            pin64(s);
            TR(c, 4);
            c.release(sk);
            first_block<16>(s, p, lim, nmu0, nmu1, l0, l1);
        }
        if (!lead) c.release(c.acquire());
    }
    uint32_t next = c.acquire();
    TR(c, 5);
#pragma unroll 1
    for (int i = 1; i < nblk; i++) {
        uint32_t sk = next;
        uint32_t sv = c.acquire();
        bar_sync(1 + c.wg, 256);
        wg_fence();
        issue_qk(s, q, c.slot_desc(sk, 16));
        issue_pv<0, PV_SPLIT>(o, p, c.slot_desc(sv, 16384));
        issue_pv<PV_SPLIT, 8>(o, p, c.slot_desc(sv, 16384));
        bar_arrive(2 - c.wg, 256);
        wg_wait<1>();
        pin64(s);
        pin_p<0, 4 * PV_SPLIT>(p);
        c.release(sk);
        float a[4] = {0.f, 0.f, 0.f, 0.f};
        exp_pack<0, 2 * PV_SPLIT>(s, p, nmu0, nmu1, a);
        pin_p<0, 4 * PV_SPLIT>(p);
        next = c.acquire();
        wg_wait<0>();
        pin_p<4 * PV_SPLIT, 32>(p);
        pin64(o);
        c.release(sv);
        exp_pack<2 * PV_SPLIT, 16>(s, p, nmu0, nmu1, a);
        float r0 = a[0] + a[1], r1 = a[2] + a[3];
        if (sums_unsafe(r0, r1)) {
            float n0 = fminf(nmu0, neg_offset(row_max<16>(s, 0))), n1 = fminf(nmu1, neg_offset(row_max<16>(s, 1)));
            const float al0 = ex2(0.5f * (n0 - nmu0)), al1 = ex2(0.5f * (n1 - nmu1));
            nmu0 = n0;
            nmu1 = n1;
#pragma unroll
            for (int t = 0; t < 16; t++) {
                o[4 * t] = o[4 * t] * al0 * al0;
                o[4 * t + 1] = o[4 * t + 1] * al0 * al0;
                o[4 * t + 2] = o[4 * t + 2] * al1 * al1;
                o[4 * t + 3] = o[4 * t + 3] * al1 * al1;
            }
            l0 = l0 * al0 * al0;
            l1 = l1 * al1 * al1;
            float b[4] = {0.f, 0.f, 0.f, 0.f};
            exp_pack<0, 16>(s, p, nmu0, nmu1, b);
            r0 = b[0] + b[1];
            r1 = b[2] + b[3];
        }
        l0 += r0;
        l1 += r1;
    }
    {
        uint32_t sv = next;
        TR(c, 6);
        bar_sync(1 + c.wg, 256);
        wg_fence();
        issue_pv<0, 8>(o, p, c.slot_desc(sv, 16384));
        if (!lead) bar_arrive(2 - c.wg, 256);
        float i0 = rcp(quad_sum(l0)) * V_UNSCALE, i1 = rcp(quad_sum(l1)) * V_UNSCALE;
        wg_wait<0>();
        pin64(o);
        TR(c, 7);
        c.release(sv);
#pragma unroll
        for (int t = 0; t < 16; t++) {
            p[2 * t] = pack_bf16(o[4 * t] * i0, o[4 * t + 1] * i0);
            p[2 * t + 1] = pack_bf16(o[4 * t + 2] * i1, o[4 * t + 3] * i1);
        }
        c.pending = 3;
        c.role ^= ROLE_FLIP;
    }
}

struct Producer {
    uint32_t sbase;
    Ring ring;
    __device__ __forceinline__ uint32_t full() const { return sbase + BAR_OFF + BAR_FULL + ring.slot * 8; }
    __device__ __forceinline__ uint32_t begin(uint32_t bytes = SLOT_BYTES) {
        mbar_wait(sbase + BAR_OFF + BAR_EMPTY + ring.slot * 8, ring.phase ^ 1);
        mbar_expect(full(), bytes);
        return sbase + ring.slot * SLOT_BYTES;
    }
    int gemm_run = 0;
    template <class LoadA>
    __device__ __forceinline__ void load_pair(const CUtensorMap* tm, int col, int krow, int rank, LoadA load_a) {
        Ring mid = ring;
        mid.advance();
        const uint32_t mid_empty = sbase + BAR_OFF + BAR_EMPTY + mid.slot * 8, mid_addr = sbase + mid.slot * SLOT_BYTES;
        uint32_t dst = begin(SLOT_BYTES + 16384) + rank * 16384;
        tma_2d_mc(dst, tm, col, krow, full());
        tma_2d_mc(dst + 8192, tm, col + 64, krow, full());
        if (gemm_run < 2) mbar_wait(mid_empty, mid.phase ^ 1);
        load_a(mid_addr, 0, full());
        ring.advance();
        lend_slot();
        dst = begin(SLOT_BYTES + 16384) + rank * 16384;
        tma_2d_mc(dst, tm, col, krow + 64, full());
        tma_2d_mc(dst + 8192, tm, col + 64, krow + 64, full());
        load_a(mid_addr + 16384, 1, full());
        ring.advance();
        gemm_run++;
    }
    __device__ __forceinline__ void lend_slot() {
        mbar_wait(sbase + BAR_OFF + BAR_EMPTY + ring.slot * 8, ring.phase ^ 1);
        mbar_arrive_one(full());
        ring.advance();
    }
    __device__ __forceinline__ void load_kv(const uint8_t* img, int rank) {
        uint32_t dst = begin();
        bulk_load_mc(dst + rank * 16384, img + rank * 16384, 16384, full());
        ring.advance();
    }
};

#define EARLY_A 1
#define ZERO_DELAY_NS 4000
#define STORE_PIECE 2048
#define STORE_GAP_NS 60
struct Item {
    int type, a, j;
    int npairs;
    int half;
    bool lends;
    __device__ __forceinline__ Item(uint32_t packed, int it) {
        const uint32_t w = __shfl_sync(0xffffffffu, packed, it);
        type = (w >> 8) & 7;
        a = (w >> 3) & 31;
        j = w & 7;
        lends = (w >> 11) & 1;
        half = (w >> 12) & 1;
        npairs = 4 + (w >> 13);
    }
    __device__ __forceinline__ int slots() const {
        return type == T_ATT ? 12 + 4 * j : 3 * npairs + (lends ? 1 : 0) + (type == T_A1 ? 1 : type == T_A2 ? 2 : 0);
    }
};
__device__ __forceinline__ int strip_of(int rank, int role) { return rank == 0 ? 3 * role : 1 + role; }

#define LOAD_ITEMS asm volatile("ld.u16 %0, [%1];" : "=r"(items) : "l"(&P.items[cluster][lane & (MAX_ITEMS - 1)]));
__global__ void __cluster_dims__(2, 1, 1) __launch_bounds__(384, 1) fused_kernel(const __grid_constant__ Params P) {
    extern __shared__ uint8_t smem_raw[];
    const uint32_t sbase = (smem_u32(smem_raw) + 1023) & ~1023u;
    const uint32_t bars = sbase + BAR_OFF;
    const int warp = __shfl_sync(0xffffffffu, threadIdx.x >> 5, 0), lane = threadIdx.x & 31;
    const int rank = blockIdx.x & 1, cluster = blockIdx.x >> 1;

    uint32_t items;
    LOAD_ITEMS
    const uint32_t code0 = P.items[cluster][0];
    const bool kv0 = ((code0 >> 8) & 7) == T_KV;
    const CUtensorMap* ta0 = kv0 ? &P.tm_ckv : &P.tm_xa;
    const int row0 = 128 * (2 * (code0 & 7) + rank);
    if (warp == 8) {
        if (lane == 0) {
            for (int i = 0; i < NSLOT; i++) {
                mbar_init(bars + BAR_FULL + i * 8, 1);
                mbar_init(bars + BAR_EMPTY + i * 8, 4);
            }
            for (int i = 0; i < 2; i++) {
                mbar_init(bars + BAR_STG_FULL + i * 8, 128);
                mbar_init(bars + BAR_STG_EMPTY + i * 8, 1);
                mbar_init(bars + BAR_STG2_FULL + i * 8, 128);
            }
            ticket_publish(bars + DEP_TICKET, 0);
            asm volatile("fence.mbarrier_init.release.cluster;" ::: "memory");
        }
        bar_arrive(5, 128);
#pragma unroll
        for (int st = 0; st < 4; st++) {
            const uint32_t bar = bars + BAR_FULL + (3 * (st >> 1) + 2 * (st & 1)) * 8;
            mbar_expect(bar, SLOT_BYTES + 16384);
            if (st < EARLY_A) tma_2d(sbase + (3 * (st >> 1) + 1) * SLOT_BYTES + (st & 1) * 16384, ta0, 64 * st, row0, bar);
        }
        mbar_arrive_one(bars + BAR_FULL + 1 * 8);
        mbar_arrive_one(bars + BAR_FULL + 4 * 8);
    } else if (warp == 9 && lane < 10) {
        asm volatile("prefetch.tensormap [%0];" ::"l"(&P.tm_xb64 + lane) : "memory");
    }
    cluster_arrive();

    if (warp >= 8) {
        asm volatile("setmaxnreg.dec.sync.aligned.u32 24;");
        cluster_wait();
        if (warp == 8) {
            const CUtensorMap* tb = kv0 ? (rank ? &P.tm_wuv : &P.tm_wuk) : &P.tm_awqkv;
            const int col = 128 * ((code0 >> 3) & 31) + (kv0 ? 0 : 512 + 512 * rank);
#pragma unroll
            for (int st = 0; st < 4; st++) {
                const int slot = 3 * (st >> 1) + 2 * (st & 1);
                tma_2d_mc(sbase + slot * SLOT_BYTES + rank * 16384, tb, col, 64 * st, bars + BAR_FULL + slot * 8);
                tma_2d_mc(sbase + slot * SLOT_BYTES + rank * 16384 + 8192, tb, col + 64, 64 * st, bars + BAR_FULL + slot * 8);
                if (st >= EARLY_A) tma_2d(sbase + (3 * (st >> 1) + 1) * SLOT_BYTES + (st & 1) * 16384, ta0, 64 * st, row0, bars + BAR_FULL + slot * 8);
            }
        }
        if (warp == 8) {
            {
                Producer pr{sbase, {0, 1}};
                pr.gemm_run = 2;
                int flip = 0;
#pragma unroll 1
                for (int it = 0; it < MAX_ITEMS - 1; it++) {
                    const Item I(items, it);
                    const int type = I.type, a = I.a, j = I.j;
                    if (type == T_END) break;
                    const int tile = 2 * j + rank;
                    if (type == T_ATT) {
                        pr.gemm_run = 0;
                        const int r0 = 256 * j + 64 * strip_of(rank, flip), r1 = 256 * j + 64 * strip_of(rank, flip ^ 1);
                        flip ^= ROLE_FLIP;
#pragma unroll 1
                        for (int ch = 0; ch < 8; ch++) {
                            uint32_t dst = pr.begin();
                            tma_2d(dst, &P.tm_xb64, 64 * ch, r0, pr.full());
                            tma_2d(dst + 8192, &P.tm_xb64, 64 * ch, r1, pr.full());
                            tma_2d_mc(dst + 16384 + rank * 8192, &P.tm_wq, 128 * a + 64 * rank, 64 * ch, pr.full());
                            pr.ring.advance();
                        }
                        uint32_t ready = ticket_wait(bars + DEP_TICKET, 64 * it + 1);
                        const uint8_t* kimg = g_K + (size_t)a * 16 * SLOT_BYTES;
                        const uint8_t* vimg = g_V + (size_t)a * 16 * SLOT_BYTES;
                        pr.load_kv(kimg + (2 * j + 1) * SLOT_BYTES, rank);
#pragma unroll 1
                        for (int n = 2 * j; n >= 0; n--) {
                            const uint32_t need = 64 * it + 1 + j - (n >> 1);
                            if (ready < need) ready = ticket_wait(bars + DEP_TICKET, need);
                            pr.load_kv(kimg + n * SLOT_BYTES, rank);
                            pr.load_kv(vimg + (n + 1) * SLOT_BYTES, rank);
                        }
                        pr.load_kv(vimg, rank);
                    } else if (type == T_OP) {
                        uint32_t ready = 0;
#pragma unroll 1
                        for (int i = 0; i < I.npairs; i++) {
                            const int h = P.op_order[j][a + i];
                            if (ready < 64 * it + i + 1) ready = ticket_wait(bars + DEP_TICKET, 64 * it + i + 1);
                            const uint8_t* img = g_ctx + (size_t)(tile * 32 + h) * SLOT_BYTES;
                            pr.load_pair(&P.tm_wo, 256 * I.half + 128 * rank, 128 * h, rank,
                                         [&](uint32_t dst, int hf, uint32_t bar) { bulk_load(dst, img + hf * 16384, 16384, bar); });
                        }
                        if (I.lends) pr.lend_slot();
                    } else {
                        const CUtensorMap* tb;
                        int col;
                        if (type == T_KV) { tb = rank ? &P.tm_wuv : &P.tm_wuk; col = 128 * a; }
                        else if (type == T_A1) { tb = &P.tm_awqkv; col = 512 + 512 * rank + 128 * a; }
                        else if (type == T_A2) { tb = &P.tm_awqkv; col = 256 * a + 128 * rank; }
                        else { tb = &P.tm_awo; col = 256 * a + 128 * rank; }
                        if (type == T_A3) ticket_wait(bars + DEP_TICKET, 64 * it + 1);
#pragma unroll 1
                        for (int p = it == 0 ? 2 : 0; p < 4; p++) {
                            const uint8_t* img = g_o + (size_t)(tile * 4 + p) * SLOT_BYTES;
                            pr.load_pair(tb, col, 128 * p, rank, [&](uint32_t dst, int hf, uint32_t bar) {
                                if (type == T_A3) bulk_load(dst, img + hf * 16384, 16384, bar);
                                else tma_2d(dst, type == T_KV ? &P.tm_ckv : &P.tm_xa, 128 * p + 64 * hf, 128 * tile, bar);
                            });
                        }
                        if (I.lends) {
                            pr.lend_slot();
                            pr.gemm_run = 0;
                        }
                        if (type == T_A1) {
                            uint32_t dst = pr.begin(4096);
                            bulk_load(dst + TAB_W_OFF, P.w_phi + a * 2048, 4096, pr.full());
                            pr.ring.advance();
                        } else if (type == T_A2) {
                            ticket_wait(bars + DEP_TICKET, 64 * it + 1);
#pragma unroll 1
                            for (int hg = 2 * a + 1; hg >= 2 * a; hg--) {
                                uint32_t dst = pr.begin(TAB_W_OFF + 4096);
                                bulk_load(dst, g_akv[lds32(bars + EPOCH_WORD) & 1] + hg * 8 * AKV_HEAD, TAB_W_OFF, pr.full());
                                bulk_load(dst + TAB_W_OFF, P.w_phi + hg * 2048, 4096, pr.full());
                                pr.ring.advance();
                            }
                        }
                    }
                }
#pragma unroll 1
                for (int i = 0; i < NSLOT; i++) {
                    mbar_wait(bars + BAR_EMPTY + pr.ring.slot * 8, pr.ring.phase ^ 1);
                    pr.ring.advance();
                }
            }
        } else if (warp < 11) {
            const int wg = warp - 9;
            bar_sync(5, 128);
            const uint32_t epoch = lds32(bars + EPOCH_WORD);
            int role = wg;
            uint32_t n1 = 0, n2 = 0, pos = 0;
#pragma unroll 1
            for (int it = 0; it < MAX_ITEMS - 1; it++) {
                const Item I(items, it);
                const int type = I.type, a = I.a, j = I.j;
                if (type == T_END) break;
                const uint32_t lent = (pos + 3 * I.npairs) % NSLOT;
                pos = (pos + I.slots()) % NSLOT;
                if (type == T_A1) {
                    const uint32_t tab = (lent + 1) % NSLOT;
                    mbar_wait(bars + BAR_STG2_FULL + wg * 8, n2++ & 1);
                    if (FENCE_IN_STORE_WARP) fence_async_smem();
                    bulk_reduce_f32(g_akv[epoch & 1] + (8 * a + 4 * wg) * AKV_HEAD, sbase + tab * SLOT_BYTES + wg * (TAB_W_OFF / 2), TAB_W_OFF / 2);
                    bulk_commit();
                    bulk_wait_read();
                    __syncwarp();
                    if (lane < 2) mbar_arrive_cta(bars + BAR_EMPTY + tab * 8, lane);
                    bulk_wait_all();
                    flag_signal(&g_flags[F_AKV + a]);
                    continue;
                }
                const int tile = 2 * j + rank;
                const int rounds = type == T_ATT ? 1 : 2;
                const bool lends = I.lends;
#pragma unroll 1
                for (int q = 0; q < rounds; q++) {
                    const int r = type == T_A2 ? 1 - q : q;
                    uint32_t stg;
                    if (r == 0 || !lends) {
                        mbar_wait(bars + BAR_STG_FULL + wg * 8, n1++ & 1);
                        stg = sbase + STG_OFF + wg * 16384;
                    } else {
                        mbar_wait(bars + BAR_STG2_FULL + wg * 8, n2++ & 1);
                        stg = sbase + lent * SLOT_BYTES + wg * 16384;
                    }
                    if (FENCE_IN_STORE_WARP) fence_async_smem();
                    if (type == T_OP) {
                        const int col = 512 + 256 * I.half + 128 * r, row = 128 * tile + 64 * wg;
                        tma_add_2d(&P.tm_out, col, row, stg);
                        tma_add_2d(&P.tm_out, col + 64, row, stg + 8192);
                    } else if (type == T_A3) {
                        const int col = 256 * a + 128 * r, row = 128 * tile + 64 * wg;
                        tma_store_2d(&P.tm_out, col, row, stg);
                        tma_store_2d(&P.tm_out, col + 64, row, stg + 8192);
                    } else {
                        uint8_t* dst;
                        if (type == T_KV) dst = (r ? g_V : g_K) + (size_t)(a * 16 + tile) * SLOT_BYTES + wg * 8192;
                        else if (type == T_A2) dst = g_o + (size_t)(tile * 4 + 2 * a + r) * SLOT_BYTES + wg * 8192;
                        else {
                            const int st = strip_of(rank, role);
                            role ^= ROLE_FLIP;
                            dst = g_ctx + (size_t)((2 * j + (st >> 1)) * 32 + a) * SLOT_BYTES + (st & 1) * 8192;
                        }
#pragma unroll 1
                        for (int o = 0; o < 16384; o += STORE_PIECE) {
                            bulk_store(dst + o + (o & 8192), stg + o, STORE_PIECE);
                            if (STORE_GAP_NS) __nanosleep(STORE_GAP_NS);
                        }
                    }
                    bulk_commit();
                    if (lends && type != T_A2 && r == 0) continue;
                    bulk_wait_read();
                    if (!lends || q == 1) mbar_arrive_one(bars + BAR_STG_EMPTY + wg * 8);
                    if (lends && r == 1) {
                        __syncwarp();
                        if (lane < 2) mbar_arrive_cta(bars + BAR_EMPTY + lent * 8, lane);
                    }
                }
                if (type == T_KV || type == T_ATT || type == T_A2) {
                    bulk_wait_all();
                    flag_signal(&g_flags[type == T_KV ? F_KV + a * 8 + j : type == T_ATT ? F_CTX + j * 32 + a : F_O + j]);
                }
            }
        } else {
            const uint32_t epoch = __shfl_sync(0xffffffffu, g_epoch[blockIdx.x], 0);
            if (lane == 0) ticket_publish(bars + EPOCH_WORD, epoch);
            bar_sync(5, 128);
            if (ZERO_DELAY_NS) __nanosleep(ZERO_DELAY_NS);
            float4* z = reinterpret_cast<float4*>(g_akv[(epoch + 1) & 1]);
            for (int i = blockIdx.x * 32 + lane; i < 32 * AKV_HEAD / 4; i += gridDim.x * 32) z[i] = make_float4(0.f, 0.f, 0.f, 0.f);
            if (lane == 0) g_epoch[blockIdx.x] = epoch + 1;
            for (int i = blockIdx.x; i < 4096; i += gridDim.x)
                *reinterpret_cast<uint4*>(P.out + (size_t)(i >> 1) * 2048 + 1024 + (i & 1) * 512 + lane * 16) = make_uint4(0, 0, 0, 0);
            __threadfence();
            __syncwarp();
            flag_signal(&g_flags[F_ZERO]);
#pragma unroll 1
            for (int it = 0; it < MAX_ITEMS - 1; it++) {
                const Item I(items, it);
                const int type = I.type, a = I.a, j = I.j;
                if (type == T_END) break;
                if (type == T_KV || type == T_A1) continue;
                if (type == T_OP) {
                    for (uint32_t n = 0; (int32_t)(ld_acquire(&g_flags[F_ZERO]) - (epoch + 1) * gridDim.x) < 0; n++) {
                        if (n > SPIN_LIMIT) { abort_launch(); break; }
                        __nanosleep(100);
                    }
                }
                const int nflags = type == T_ATT ? j + 1 : type == T_OP ? I.npairs : type == T_A2 ? 2 : 1;
                const uint32_t* flag = &g_flags[type == T_ATT ? F_KV + a * 8 : type == T_OP ? F_CTX + j * 32 : type == T_A2 ? F_AKV + 2 * a : F_O + j] +
                                       (type == T_OP ? P.op_order[j][(a + lane) & 31] : type == T_ATT ? (j - lane) & 7 : lane);
                const uint32_t target = (epoch + 1) * (type == T_A2 ? 32 : type == T_A3 ? 8 : 4);
                int done = 0;
                for (uint32_t n = 0;; n++) {
                    const bool ok = lane >= nflags || (int32_t)(ld_acquire(flag) - target) >= 0;
                    const uint32_t miss = ~__ballot_sync(0xffffffffu, ok);
                    const int ready = miss ? (type == T_A2 ? 0 : __ffs(miss) - 1) : 32;
                    if (ready > done) {
                        done = ready;
                        fence_async_global();
                        __syncwarp();
                        if (lane == 0) ticket_publish(bars + DEP_TICKET, 64 * it + ready);
                    }
                    if (!miss) break;
                    if (n > SPIN_LIMIT) { abort_launch(); break; }
                    __nanosleep(100);
                }
            }
        }
    } else {
        asm volatile("setmaxnreg.inc.sync.aligned.u32 240;");
        cluster_wait();
        Consumer c;
        c.sbase = sbase;
        c.wg = warp >> 2;
        c.tid = threadIdx.x & 127;
        c.stg = sbase + STG_OFF + c.wg * 16384;
        {
            const int row = (warp & 3) * 16 + ((lane >> 3) & 1) * 8 + (lane & 7);
            c.stm_off = row * 128 + (((lane >> 4) ^ (lane & 7)) * 16);
        }
        c.nstores = 0;
        c.pending = 0;
        c.role = c.wg;
        uint32_t pend[32];
#pragma unroll
        for (int i = 0; i < 32; i++) pend[i] = 0;
        c.ring = {0, 0};
#pragma unroll 1
        for (int it = 0; it < MAX_ITEMS - 1; it++) {
            const Item I(items, it);
            const int type = I.type, j = I.j;
            if (type == T_END) break;
            c.make_uniform();
            if (type == T_ATT) {
                attention_item(c, j, rank, pend);
            } else {
                float acc[128];
                if ((type == T_OP || type == T_A3) && (c.pending & 2)) c.flush(pend);
                const bool plain = type != T_A1 && type != T_A2;
                gemm_mainloop(c, acc, I.npairs, pend);
#pragma unroll
                for (int i = 0; i < 32; i++) pend[i] = pack_bf16(acc[2 * i], acc[2 * i + 1]);
                c.write_first(pend);
                if (plain) c.submit_first();
#pragma unroll
                for (int i = 0; i < 32; i++) pend[i] = pack_bf16(acc[64 + 2 * i], acc[65 + 2 * i]);
                if (type == T_KV) {
#pragma unroll
                    for (int i = 0; i < 32; i++) asm("mul.bf16x2 %0, %0, %1;" : "+r"(pend[i]) : "r"(V_SCALE_BF16X2));
                }
                if (!I.lends) {
                    c.pending = type == T_KV ? 3 : 1;
                } else if (plain) {
                    c.write_second(pend);
                    c.submit_second();
                } else {
                    const uint32_t lent = c.write_second(pend);
                    TR(c, 12);
                    bar_sync(3, 256);
                    TR(c, 13);
                    if (type == T_A1) {
                        const uint32_t tab = c.acquire();
                        TR(c, 14);
                        a1_epilogue(sbase + STG_OFF, c.slot_addr(lent), c.slot_addr(tab), warp, lane);
                        TR(c, 15);
                        c.submit_second();
                        bar_sync(3, 256);
                        c.release(lent);
                    } else {
#pragma unroll 1
                        for (int r = 1; r >= 0; r--) {
                            const uint32_t tab = c.acquire();
                            TR(c, 14);
                                a2_epilogue(r ? c.slot_addr(lent) : sbase + STG_OFF, c.slot_addr(tab), warp, lane);
                            if (!FENCE_IN_STORE_WARP) fence_async_smem();
                            bar_sync(3, 256);
                            c.release(tab);
                            mbar_arrive(bars + (r ? BAR_STG2_FULL : BAR_STG_FULL) + c.wg * 8);
                        }
                        c.nstores++;
                        TR(c, 15);
                    }
                }
            }
        }
        c.flush(pend);
    }
}

typedef CUresult (*EncodeFn)(CUtensorMap*, CUtensorMapDataType, cuuint32_t, void*, const cuuint64_t*, const cuuint64_t*,
                             const cuuint32_t*, const cuuint32_t*, CUtensorMapInterleave, CUtensorMapSwizzle,
                             CUtensorMapL2promotion, CUtensorMapFloatOOBfill);

void make_map(EncodeFn fn, CUtensorMap* tm, const void* ptr, int rows, int cols, int box_rows) {
    cuuint64_t dims[2] = {(cuuint64_t)cols, (cuuint64_t)rows};
    cuuint64_t strides[1] = {(cuuint64_t)cols * 2};
    cuuint32_t box[2] = {64, (cuuint32_t)box_rows};
    cuuint32_t estr[2] = {1, 1};
    fn(tm, CU_TENSOR_MAP_DATA_TYPE_BFLOAT16, 2, const_cast<void*>(ptr), dims, strides, box, estr, CU_TENSOR_MAP_INTERLEAVE_NONE,
       CU_TENSOR_MAP_SWIZZLE_128B, CU_TENSOR_MAP_L2_PROMOTION_L2_256B, CU_TENSOR_MAP_FLOAT_OOB_FILL_NONE);
}

const uint16_t kSchedule[1312] = {
    0x030f, 0x0106, 0x00a9, 0x00c6, 0x040e, 0x002c, 0x01c2, 0x01e4, 0xa287, 0x0700, 0x0700, 0x0700, 0x0700, 0x0700, 0x0700, 0x0700,
    0x000e, 0x0303, 0x01d5, 0x0164, 0x0177, 0x01b2, 0xd22d, 0x0700, 0x0700, 0x0700, 0x0700, 0x0700, 0x0700, 0x0700, 0x0700, 0x0700,
    0x005c, 0x008b, 0x01ce, 0x0076, 0x0161, 0x0188, 0x00ee, 0x01c1, 0x01e5, 0xd2b3, 0x0700, 0x0700, 0x0700, 0x0700, 0x0700, 0x0700,
    0x00cc, 0x031e, 0x010c, 0x0165, 0x002d, 0x0051, 0x004a, 0x00ea, 0x0040, 0x019a, 0x9230, 0x0700, 0x0700, 0x0700, 0x0700, 0x0700,
    0x00d4, 0x0312, 0x010b, 0x010a, 0x01ac, 0x00b1, 0x00e2, 0x0048, 0x01f2, 0x01e8, 0x8231, 0x0700, 0x0700, 0x0700, 0x0700, 0x0700,
    0x00bc, 0x0085, 0x010f, 0x00c4, 0x017e, 0x019f, 0x0504, 0x0509, 0x0700, 0x0700, 0x0700, 0x0700, 0x0700, 0x0700, 0x0700, 0x0700,
    0x000a, 0x0019, 0x016e, 0x007d, 0x0110, 0x0073, 0x00e7, 0x00b2, 0x01db, 0x012a, 0xd2b0, 0x0700, 0x0700, 0x0700, 0x0700, 0x0700,
    0x00be, 0x030d, 0x0114, 0x011c, 0x00fc, 0x00b6, 0x01fd, 0x0402, 0x050b, 0x050f, 0x0700, 0x0700, 0x0700, 0x0700, 0x0700, 0x0700,
    0x0301, 0x0124, 0x01c9, 0x0131, 0x018a, 0x01c4, 0x019d, 0x729a, 0x0700, 0x0700, 0x0700, 0x0700, 0x0700, 0x0700, 0x0700, 0x0700,
    0x005b, 0x00d2, 0x01cf, 0x018d, 0x01a1, 0x01b7, 0xa2b9, 0x0700, 0x0700, 0x0700, 0x0700, 0x0700, 0x0700, 0x0700, 0x0700, 0x0700,
    0x0020, 0x0307, 0x01ca, 0x011e, 0x009a, 0x004d, 0x01f6, 0x0198, 0xb206, 0x0700, 0x0700, 0x0700, 0x0700, 0x0700, 0x0700, 0x0700,
    0x000c, 0x003a, 0x01d6, 0x0112, 0x00c0, 0x01a8, 0x01a0, 0x0173, 0x014a, 0x01b0, 0x4243, 0x0700, 0x0700, 0x0700, 0x0700, 0x0700,
    0x00c8, 0x0300, 0x0137, 0x007a, 0x01a9, 0x00ed, 0x0049, 0x0099, 0x01d8, 0x0150, 0x0141, 0x629c, 0x0700, 0x0700, 0x0700, 0x0700,
    0x0022, 0x0059, 0x0117, 0x0077, 0x00ff, 0x00da, 0x00b7, 0x004b, 0x01f4, 0x0199, 0x9201, 0x0700, 0x0700, 0x0700, 0x0700, 0x0700,
    0x0007, 0x0012, 0x00d0, 0x008c, 0x0062, 0x011d, 0x004f, 0x0054, 0x0157, 0xe273, 0x0700, 0x0700, 0x0700, 0x0700, 0x0700, 0x0700,
    0x0027, 0x006a, 0x01be, 0x00a7, 0x00a4, 0x0050, 0x00ef, 0x00d8, 0x002a, 0x012d, 0xc255, 0x0700, 0x0700, 0x0700, 0x0700, 0x0700,
    0x006d, 0x0011, 0x01bf, 0x0403, 0x0057, 0x0071, 0x00b4, 0x0028, 0x01b3, 0xf27d, 0x0700, 0x0700, 0x0700, 0x0700, 0x0700, 0x0700,
    0x0024, 0x0003, 0x01cd, 0x007e, 0x0094, 0x0074, 0x009f, 0x009e, 0x01fb, 0x0145, 0x5281, 0x0700, 0x0700, 0x0700, 0x0700, 0x0700,
    0x003b, 0x0030, 0x01bb, 0x0103, 0x00c5, 0x0052, 0x00f9, 0x01a2, 0x019e, 0x9241, 0x0700, 0x0700, 0x0700, 0x0700, 0x0700, 0x0700,
    0x0006, 0x031f, 0x01cb, 0x0135, 0x0056, 0x00f8, 0x01de, 0x01e9, 0x8204, 0x0700, 0x0700, 0x0700, 0x0700, 0x0700, 0x0700, 0x0700,
    0x0015, 0x0010, 0x0168, 0x016a, 0x01b9, 0x0181, 0x0118, 0x00e6, 0x009c, 0x014f, 0xa246, 0x0700, 0x0700, 0x0700, 0x0700, 0x0700,
    0x030b, 0x016f, 0x0313, 0x00a1, 0x00fb, 0x0408, 0x00eb, 0x0098, 0x01eb, 0x62cf, 0x0700, 0x0700, 0x0700, 0x0700, 0x0700, 0x0700,
    0x00bd, 0x0063, 0x015d, 0x018f, 0x01c0, 0x012f, 0xf2af, 0x0700, 0x0700, 0x0700, 0x0700, 0x0700, 0x0700, 0x0700, 0x0700, 0x0700,
    0x0308, 0x030a, 0x013a, 0x0102, 0x017f, 0x014e, 0xd28e, 0x0700, 0x0700, 0x0700, 0x0700, 0x0700, 0x0700, 0x0700, 0x0700, 0x0700,
    0x00cf, 0x0037, 0x015f, 0x0130, 0x00fd, 0x040f, 0x009b, 0x0042, 0x01b4, 0x3205, 0x0503, 0x0700, 0x0700, 0x0700, 0x0700, 0x0700,
    0x00d6, 0x0008, 0x015e, 0x0311, 0x0196, 0x0172, 0x0152, 0xd263, 0x0700, 0x0700, 0x0700, 0x0700, 0x0700, 0x0700, 0x0700, 0x0700,
    0x005e, 0x031a, 0x010e, 0x00a5, 0x00c3, 0x00f4, 0x0190, 0x0174, 0x01ec, 0x52d5, 0x0700, 0x0700, 0x0700, 0x0700, 0x0700, 0x0700,
    0x003e, 0x0081, 0x0083, 0x015a, 0x00ab, 0x0095, 0x018b, 0x01c3, 0x01b5, 0x0505, 0x32de, 0x0700, 0x0700, 0x0700, 0x0700, 0x0700,
    0x00ca, 0x0302, 0x008e, 0x00ad, 0x0061, 0x0134, 0x0160, 0x0191, 0x01e7, 0x0500, 0x42d4, 0x0700, 0x0700, 0x0700, 0x0700, 0x0700,
    0x0069, 0x00b8, 0x0116, 0x018e, 0x01df, 0x3203, 0xa202, 0x0700, 0x0700, 0x0700, 0x0700, 0x0700, 0x0700, 0x0700, 0x0700, 0x0700,
    0x0017, 0x0001, 0x0318, 0x01ba, 0x00aa, 0x0100, 0x0079, 0x009d, 0x004c, 0x01fc, 0x0129, 0xe244, 0x0700, 0x0700, 0x0700, 0x0700,
    0x0039, 0x0038, 0x00af, 0x0123, 0x008a, 0x0093, 0x01ab, 0x0175, 0x0409, 0x0507, 0x52d4, 0x0700, 0x0700, 0x0700, 0x0700, 0x0700,
    0x006c, 0x0086, 0x0107, 0x007b, 0x0078, 0x00f5, 0x0192, 0x0156, 0xc270, 0x0700, 0x0700, 0x0700, 0x0700, 0x0700, 0x0700, 0x0700,
    0x0005, 0x0009, 0x0032, 0x0186, 0x018c, 0x01dc, 0x01e3, 0xd22f, 0x0700, 0x0700, 0x0700, 0x0700, 0x0700, 0x0700, 0x0700, 0x0700,
    0x0004, 0x0002, 0x0122, 0x011f, 0x01c7, 0x014c, 0xb202, 0x0700, 0x0700, 0x0700, 0x0700, 0x0700, 0x0700, 0x0700, 0x0700, 0x0700,
    0x00cd, 0x001a, 0x0126, 0x01b8, 0x0075, 0x0189, 0x00f3, 0x00b0, 0x040c, 0x01e2, 0xd23c, 0x0700, 0x0700, 0x0700, 0x0700, 0x0700,
    0x0016, 0x0084, 0x0314, 0x0060, 0x0121, 0x0101, 0x01aa, 0x0178, 0x0044, 0x00e8, 0x0154, 0xa28a, 0x0700, 0x0700, 0x0700, 0x0700,
    0x0068, 0x0080, 0x01bc, 0x0184, 0x00a0, 0x0072, 0x0070, 0x00e1, 0x01ef, 0x42d2, 0x0700, 0x0700, 0x0700, 0x0700, 0x0700, 0x0700,
    0x006b, 0x000d, 0x015c, 0x0167, 0x01ff, 0x01ea, 0x924e, 0x0700, 0x0700, 0x0700, 0x0700, 0x0700, 0x0700, 0x0700, 0x0700, 0x0700,
    0x00bf, 0x00d3, 0x0031, 0x01d3, 0x0096, 0x0132, 0x00fa, 0x0045, 0x00b3, 0x0041, 0x012c, 0xb28c, 0x0700, 0x0700, 0x0700, 0x0700,
    0x00ce, 0x0309, 0x013d, 0x0400, 0x00a2, 0x0193, 0x01b6, 0xc237, 0x0700, 0x0700, 0x0700, 0x0700, 0x0700, 0x0700, 0x0700, 0x0700,
    0x030e, 0x01c8, 0x0187, 0x00c2, 0x00f7, 0x0053, 0x00f0, 0x01f9, 0x012b, 0x722b, 0x050a, 0x0700, 0x0700, 0x0700, 0x0700, 0x0700,
    0x006f, 0x0315, 0x0067, 0x008f, 0x0185, 0x0195, 0x01e6, 0x050d, 0x42d5, 0x0700, 0x0700, 0x0700, 0x0700, 0x0700, 0x0700, 0x0700,
    0x000b, 0x0319, 0x01cc, 0x0109, 0x0090, 0x00d9, 0x0047, 0x01a3, 0x01ee, 0x3207, 0x0700, 0x0700, 0x0700, 0x0700, 0x0700, 0x0700,
    0x00ba, 0x0035, 0x013f, 0x00c7, 0x0092, 0x0194, 0x0171, 0x01ed, 0x52d2, 0x0700, 0x0700, 0x0700, 0x0700, 0x0700, 0x0700, 0x0700,
    0x006e, 0x031c, 0x001c, 0x01d2, 0x0183, 0x00f6, 0x00e4, 0x0405, 0x0153, 0xa271, 0x050e, 0x0700, 0x0700, 0x0700, 0x0700, 0x0700,
    0x00cb, 0x0316, 0x0115, 0x0163, 0x002f, 0x017a, 0x00e9, 0x0407, 0x01e1, 0x7204, 0x0700, 0x0700, 0x0700, 0x0700, 0x0700, 0x0700,
    0x00d7, 0x0087, 0x0169, 0x0104, 0x01ad, 0x00f2, 0x00e3, 0x0147, 0x5200, 0x0700, 0x0700, 0x0700, 0x0700, 0x0700, 0x0700, 0x0700,
    0x003d, 0x00ac, 0x016c, 0x0108, 0x0182, 0x0180, 0x01a5, 0x0146, 0x42a5, 0x0700, 0x0700, 0x0700, 0x0700, 0x0700, 0x0700, 0x0700,
    0x005d, 0x0058, 0x01d7, 0x0111, 0x00dd, 0x0055, 0x00b5, 0x00ec, 0x01fa, 0x0149, 0xc205, 0x0700, 0x0700, 0x0700, 0x0700, 0x0700,
    0x00d5, 0x0033, 0x013e, 0x01ae, 0x0179, 0x01f5, 0x527f, 0x42d6, 0x0700, 0x0700, 0x0700, 0x0700, 0x0700, 0x0700, 0x0700, 0x0700,
    0x0014, 0x001f, 0x0304, 0x0158, 0x0159, 0x01d1, 0x01a7, 0x0155, 0xa28e, 0x0700, 0x0700, 0x0700, 0x0700, 0x0700, 0x0700, 0x0700,
    0x0305, 0x0066, 0x013c, 0x011b, 0x017d, 0x0043, 0x01f3, 0x01e0, 0x0508, 0x0506, 0x0700, 0x0700, 0x0700, 0x0700, 0x0700, 0x0700,
    0x003f, 0x001b, 0x007f, 0x0113, 0x0166, 0x01a4, 0x01f8, 0x01f0, 0x01b1, 0x050c, 0x0501, 0x0700, 0x0700, 0x0700, 0x0700, 0x0700,
    0x0306, 0x001d, 0x01d4, 0x0138, 0x011a, 0x040d, 0x002b, 0x0029, 0x014d, 0x8230, 0x0700, 0x0700, 0x0700, 0x0700, 0x0700, 0x0700,
    0x00b9, 0x00c9, 0x001e, 0x0136, 0x0119, 0x017c, 0x01da, 0x014b, 0x9270, 0x0700, 0x0700, 0x0700, 0x0700, 0x0700, 0x0700, 0x0700,
    0x00bb, 0x0013, 0x0064, 0x016b, 0x0139, 0x0404, 0x017b, 0x00e0, 0x0170, 0x019b, 0x82c0, 0x0700, 0x0700, 0x0700, 0x0700, 0x0700,
    0x005f, 0x031d, 0x015b, 0x0097, 0x0406, 0x00de, 0x002e, 0x01f7, 0x0148, 0xd24a, 0x0700, 0x0700, 0x0700, 0x0700, 0x0700, 0x0700,
    0x0026, 0x0036, 0x0125, 0x01d0, 0x00a8, 0x0091, 0x0046, 0x004e, 0x00f1, 0x040b, 0x0401, 0x0140, 0x4207, 0x0700, 0x0700, 0x0700,
    0x0021, 0x00d1, 0x008d, 0x0105, 0x0088, 0x00df, 0x01a6, 0x01d9, 0x0143, 0x4201, 0x0700, 0x0700, 0x0700, 0x0700, 0x0700, 0x0700,
    0x005a, 0x0065, 0x01bd, 0x01af, 0x01fe, 0x0128, 0x8203, 0x0502, 0x0700, 0x0700, 0x0700, 0x0700, 0x0700, 0x0700, 0x0700, 0x0700,
    0x0025, 0x0034, 0x016d, 0x0133, 0x00db, 0x00e5, 0x01dd, 0x0144, 0x4200, 0x0700, 0x0700, 0x0700, 0x0700, 0x0700, 0x0700, 0x0700,
    0x003c, 0x031b, 0x0000, 0x00ae, 0x0018, 0x00a6, 0x0162, 0x01c6, 0x01f1, 0x040a, 0x824a, 0x0700, 0x0700, 0x0700, 0x0700, 0x0700,
    0x0023, 0x0310, 0x0120, 0x013b, 0x0089, 0x00a3, 0x00c1, 0x0176, 0x019c, 0x8206, 0x0700, 0x0700, 0x0700, 0x0700, 0x0700, 0x0700,
    0x000f, 0x0317, 0x0082, 0x010d, 0x0197, 0x012e, 0xd2b1, 0x0700, 0x0700, 0x0700, 0x0700, 0x0700, 0x0700, 0x0700, 0x0700, 0x0700,
    0x030c, 0x0127, 0x007c, 0x00fe, 0x00dc, 0x01c5, 0x0151, 0x0142, 0x62cb, 0x0700, 0x0700, 0x0700, 0x0700, 0x0700, 0x0700, 0x0700,
    0x0019, 0x000d, 0x0004, 0x000b, 0x0001, 0x001a, 0x0007, 0x0017, 0x0006, 0x0000, 0x0002, 0x0003, 0x0010, 0x0011, 0x000c, 0x0015,
    0x000f, 0x0012, 0x0018, 0x0014, 0x001f, 0x000e, 0x001b, 0x001e, 0x0005, 0x000a, 0x0009, 0x0013, 0x001c, 0x001d, 0x0016, 0x0008,
    0x000d, 0x000b, 0x0004, 0x0019, 0x0017, 0x0007, 0x0001, 0x001a, 0x0000, 0x0006, 0x0002, 0x0010, 0x0003, 0x000c, 0x0011, 0x0015,
    0x0012, 0x000f, 0x0014, 0x0018, 0x001f, 0x000e, 0x001b, 0x001e, 0x000a, 0x0005, 0x0009, 0x0016, 0x0013, 0x001d, 0x001c, 0x0008,
    0x0004, 0x0019, 0x000d, 0x000b, 0x0007, 0x0017, 0x001a, 0x0001, 0x0000, 0x0002, 0x0010, 0x0006, 0x0003, 0x000c, 0x0015, 0x0011,
    0x0012, 0x000f, 0x0014, 0x0018, 0x001b, 0x000e, 0x001f, 0x001e, 0x0016, 0x0005, 0x000a, 0x001c, 0x0009, 0x001d, 0x0013, 0x0008,
    0x0017, 0x0001, 0x000b, 0x0019, 0x0004, 0x001a, 0x000d, 0x0002, 0x0007, 0x0000, 0x0006, 0x0003, 0x0010, 0x000c, 0x0011, 0x0015,
    0x000f, 0x0012, 0x0018, 0x0014, 0x001f, 0x000e, 0x001b, 0x000a, 0x0016, 0x0005, 0x001e, 0x001c, 0x0009, 0x0013, 0x001d, 0x0008,
    0x0004, 0x0017, 0x000b, 0x000d, 0x0001, 0x0019, 0x001a, 0x0007, 0x0002, 0x0000, 0x0010, 0x0003, 0x0006, 0x000c, 0x0011, 0x0015,
    0x000f, 0x0012, 0x0014, 0x0018, 0x001b, 0x000e, 0x001f, 0x001e, 0x0016, 0x0005, 0x000a, 0x001c, 0x0009, 0x0013, 0x0008, 0x001d,
    0x000d, 0x000b, 0x0004, 0x0017, 0x0019, 0x0002, 0x001a, 0x0007, 0x0000, 0x0001, 0x0010, 0x0003, 0x0006, 0x000c, 0x0011, 0x0015,
    0x000f, 0x0012, 0x0014, 0x0018, 0x001b, 0x000e, 0x001f, 0x001e, 0x001c, 0x0005, 0x0016, 0x000a, 0x0009, 0x0013, 0x0008, 0x001d,
    0x0000, 0x0017, 0x0007, 0x000b, 0x000d, 0x0004, 0x001a, 0x0002, 0x0019, 0x0001, 0x0006, 0x0010, 0x0003, 0x000c, 0x0015, 0x0011,
    0x000f, 0x0012, 0x0014, 0x0018, 0x000e, 0x001f, 0x001b, 0x001e, 0x000a, 0x001c, 0x0005, 0x0016, 0x0009, 0x0013, 0x0008, 0x001d,
    0x0004, 0x000d, 0x001a, 0x0007, 0x0017, 0x0019, 0x000b, 0x0000, 0x0002, 0x0001, 0x0010, 0x0006, 0x0003, 0x000c, 0x0011, 0x0015,
    0x0012, 0x000f, 0x0014, 0x0018, 0x000e, 0x001f, 0x001b, 0x001e, 0x000a, 0x0005, 0x001c, 0x0009, 0x0016, 0x0013, 0x0008, 0x001d,
};

Params P;

void load_schedule(const uint16_t* t) {
    const uint16_t* order = t + MAX_CLUSTERS * MAX_ITEMS;
    for (int c = 0; c < MAX_CLUSTERS; c++)
        for (int i = 0; i < MAX_ITEMS; i++) {
            const uint32_t code = t[c * MAX_ITEMS + i], type = (code >> 8) & 7;
            const bool last = i + 1 == MAX_ITEMS || ((t[c * MAX_ITEMS + i + 1] >> 8) & 7) == T_END;
            const bool lends = type == T_A1 || type == T_A2 || (type != T_ATT && last);
            P.items[c][i] = code | (lends ? 1u << 11 : 0);
        }
    for (int i = 0; i < 256; i++) P.op_order[i >> 5][i & 31] = (uint8_t)order[i];
}

}

extern "C" void kernel_launch(void* const* d_in, const int* in_sizes, int n_in, void* d_out, int out_size) {
    static bool ready = false;
    if (!ready) {
        void* fp = nullptr;
        cudaDriverEntryPointQueryResult qr;
        cudaGetDriverEntryPoint("cuTensorMapEncodeTiled", &fp, cudaEnableDefault, &qr);
        EncodeFn fn = (EncodeFn)fp;
        make_map(fn, &P.tm_xa, d_in[0], 2048, 512, 128);
        make_map(fn, &P.tm_awqkv, d_in[1], 512, 1536, 64);
        P.w_phi = (const __nv_bfloat16*)d_in[2];
        make_map(fn, &P.tm_awo, d_in[3], 512, 512, 64);
        make_map(fn, &P.tm_xb64, d_in[4], 2048, 512, 64);
        make_map(fn, &P.tm_ckv, d_in[5], 2048, 512, 128);
        make_map(fn, &P.tm_wq, d_in[6], 512, 4096, 64);
        make_map(fn, &P.tm_wuk, d_in[7], 512, 4096, 64);
        make_map(fn, &P.tm_wuv, d_in[8], 512, 4096, 64);
        make_map(fn, &P.tm_wo, d_in[9], 4096, 512, 64);
        make_map(fn, &P.tm_out, d_out, 2048, 1024, 64);
        P.out = (uint8_t*)d_out;
        load_schedule(kSchedule);
        cudaFuncSetAttribute(fused_kernel, cudaFuncAttributeMaxDynamicSharedMemorySize, SMEM_BYTES);
        ready = true;
    }
    fused_kernel<<<2 * MAX_CLUSTERS, 384, SMEM_BYTES>>>(P);
}
```
